```python
import torch

def _softmax(x, axis=-1):
    return torch.softmax(x, dim=axis)
def _gelu(x):
    return torch.nn.functional.gelu(x, approximate="tanh")
def _silu(x):
    return torch.nn.functional.silu(x)
def _sigmoid(x):
    return torch.sigmoid(x)
def _layernorm(x, axis=-1, eps=1e-5):
    m = x.mean(dim=axis, keepdim=True)
    v = x.var(dim=axis, keepdim=True, unbiased=False)
    return (x - m) / torch.sqrt(v + eps)
def _scatter_add(tgt, idx, src, axis=0):
    return tgt.clone().index_add_(axis, idx, src)
def _segment_sum(src, seg, n):
    out = torch.zeros((n,) + src.shape[1:], dtype=src.dtype)
    return out.index_add_(0, seg, src)
def _pad(x, pw):
    flat = tuple(v for pair in reversed(pw) for v in pair)
    return torch.nn.functional.pad(x, flat)

kernel_name = 'standalone__edge_featured_mpnn_gatedgcn__graph'

def setup_inputs():

    _w = (lambda a: (lambda t: t.to(torch.bfloat16) if t.is_floating_point() else t)(torch.as_tensor(a)))
    N, deg, D, De = 10000, 64, 64, max(16, 1)
    E = N * deg
    return {
        "x": _w((lambda *s: torch.randn(*s, dtype=torch.bfloat16) * 0.8)(N, D)),
        "e_attr": _w((lambda *s: torch.randn(*s, dtype=torch.bfloat16) * 0.8)(E, De)),
        "src": _w((lambda lo, hi, *s: torch.randint(lo, hi, s))(0, N, E).to(torch.int64)),
        "dst": _w((lambda lo, hi, *s: torch.randint(lo, hi, s))(0, N, E).to(torch.int64)),
        "w_a": _w((lambda *s: torch.randn(*s, dtype=torch.bfloat16) * 0.8)(D, D)),
        "w_b": _w((lambda *s: torch.randn(*s, dtype=torch.bfloat16) * 0.8)(D, D)),
        "w_c": _w((lambda *s: torch.randn(*s, dtype=torch.bfloat16) * 0.8)(De, D)),
        "w_u": _w((lambda *s: torch.randn(*s, dtype=torch.bfloat16) * 0.05)(D, D)),
        "w_v": _w((lambda *s: torch.randn(*s, dtype=torch.bfloat16) * 0.05)(D, D)),
    }

def reference(x, e_attr, src, dst, w_a, w_b, w_c, w_u, w_v):
    N, D = x.shape
    hv = x @ w_v
    g = x[dst] @ w_a + x[src] @ w_b + e_attr @ w_c
    eta = _sigmoid(g)
    denom = _segment_sum(eta, dst, N) + 1e-6
    eta_n = eta / denom[dst]
    agg = _segment_sum(eta_n * hv[src], dst, N)
    z = x @ w_u + agg
    relu_z = torch.where(z > 0, z, 0 * z)
    return x + relu_z
```

```cpp
#include <cuda_runtime.h>
#include <cuda_bf16.h>
#include <stdint.h>

namespace {

constexpr int kN = 10000;
constexpr int kE = 640000;
constexpr int kCTAs = 132;
constexpr int kNPC = 76;
constexpr int kCH = 4852;
constexpr int kRecCap = 4992;
constexpr int kThreads = 512;
constexpr int kNWG = 3;
constexpr int kStages = 4;
constexpr int kLMax = 30;
constexpr int kStageB = 11264;
constexpr int kExtraCap = 512;

constexpr int SM_STAGE = 0;
constexpr int SM_IDENT = SM_STAGE + kNWG * kStages * kStageB;
constexpr int SM_LEID = SM_IDENT + 1024;
constexpr int SM_LSRC = SM_LEID + kNWG * kLMax * 64 * 4;
constexpr int SM_META = SM_LSRC + kNWG * kLMax * 64 * 2;
constexpr int SM_ACC = SM_META + 768;
constexpr int SM_ATAB = SM_ACC + 77 * 512;
constexpr int SM_UTAB = SM_ATAB + 80 * 128;
constexpr int SM_MISC = SM_UTAB + 80 * 128;
constexpr int SM_BAR = SM_MISC;
constexpr int SM_CNT = SM_BAR + 192;
constexpr int SM_VARS = SM_CNT + 320;
constexpr int SM_TOTAL = SM_VARS + 64;
constexpr int SC_SORT = 0;
constexpr int SC_W = 40960;
constexpr int SC_XOWN = SC_W + 4 * 8192 + 2048;
constexpr int SC_HIST = SC_XOWN + 80 * 128;
constexpr int SC_EXTRA = SC_HIST + 2048;
constexpr int SC_OST = SC_EXTRA + kExtraCap * 12;
static_assert(SC_XOWN % 1024 == 0, "align");
static_assert(SC_OST + 1024 < SM_IDENT, "scratch");
static_assert(SM_TOTAL <= 232448, "smem");

__device__ unsigned long long g_hdr[kCTAs * kCTAs];
__device__ __align__(16) unsigned long long g_rec[kCTAs * kRecCap];
__device__ unsigned int g_epoch[kCTAs];
__device__ __align__(16) const unsigned int g_flag[4] = {0x00003F80u, 0u, 0u, 0u};
#define STAMP(i)
#define STAMPT(t, i)

__device__ __forceinline__ void wg_fence() { asm volatile("wgmma.fence.sync.aligned;" ::: "memory"); }
__device__ __forceinline__ void wg_commit() { asm volatile("wgmma.commit_group.sync.aligned;" ::: "memory"); }
template <int N> __device__ __forceinline__ void wg_wait() { asm volatile("wgmma.wait_group.sync.aligned %0;" ::"n"(N) : "memory"); }
__device__ __forceinline__ void proxy_fence() { asm volatile("fence.proxy.async.shared::cta;" ::: "memory"); }

__device__ __forceinline__ void wgmma_n64(float (&d)[32], const uint32_t (&a)[4], uint64_t desc, int scale_d) {
    asm volatile(
        "{\n.reg .pred p;\nsetp.ne.b32 p, %37, 0;\n"
        "wgmma.mma_async.sync.aligned.m64n64k16.f32.bf16.bf16 "
        "{%0,%1,%2,%3,%4,%5,%6,%7,%8,%9,%10,%11,%12,%13,%14,%15,%16,%17,%18,%19,%20,%21,%22,%23,%24,%25,%26,%27,%28,%29,%30,%31},"
        "{%32,%33,%34,%35}, %36, p, 1, 1, 0;\n}\n"
        : "+f"(d[0]), "+f"(d[1]), "+f"(d[2]), "+f"(d[3]), "+f"(d[4]), "+f"(d[5]), "+f"(d[6]), "+f"(d[7]),
          "+f"(d[8]), "+f"(d[9]), "+f"(d[10]), "+f"(d[11]), "+f"(d[12]), "+f"(d[13]), "+f"(d[14]), "+f"(d[15]),
          "+f"(d[16]), "+f"(d[17]), "+f"(d[18]), "+f"(d[19]), "+f"(d[20]), "+f"(d[21]), "+f"(d[22]), "+f"(d[23]),
          "+f"(d[24]), "+f"(d[25]), "+f"(d[26]), "+f"(d[27]), "+f"(d[28]), "+f"(d[29]), "+f"(d[30]), "+f"(d[31])
        : "r"(a[0]), "r"(a[1]), "r"(a[2]), "r"(a[3]), "l"(desc), "r"(scale_d));
}
__device__ __forceinline__ void wgmma_n40(float (&d)[20], const uint32_t (&a)[4], uint64_t desc, int scale_d) {
    asm volatile(
        "{\n.reg .pred p;\nsetp.ne.b32 p, %25, 0;\n"
        "wgmma.mma_async.sync.aligned.m64n40k16.f32.bf16.bf16 "
        "{%0,%1,%2,%3,%4,%5,%6,%7,%8,%9,%10,%11,%12,%13,%14,%15,%16,%17,%18,%19},"
        "{%20,%21,%22,%23}, %24, p, 1, 1, 0;\n}\n"
        : "+f"(d[0]), "+f"(d[1]), "+f"(d[2]), "+f"(d[3]), "+f"(d[4]), "+f"(d[5]), "+f"(d[6]), "+f"(d[7]),
          "+f"(d[8]), "+f"(d[9]), "+f"(d[10]), "+f"(d[11]), "+f"(d[12]), "+f"(d[13]), "+f"(d[14]), "+f"(d[15]),
          "+f"(d[16]), "+f"(d[17]), "+f"(d[18]), "+f"(d[19])
        : "r"(a[0]), "r"(a[1]), "r"(a[2]), "r"(a[3]), "l"(desc), "r"(scale_d));
}
template <int R> __device__ __forceinline__ void fence_regs(float (&d)[R]) {
#pragma unroll
    for (int i = 0; i < R; i++) asm volatile("" : "+f"(d[i])::"memory");
}
__device__ __forceinline__ uint64_t mkdesc(uint32_t addr, uint32_t lbo, uint32_t sbo, uint32_t swz) {
    return (uint64_t)((addr & 0x3FFFF) >> 4) | ((uint64_t)(lbo >> 4) << 16) | ((uint64_t)(sbo >> 4) << 32) | ((uint64_t)swz << 62);
}
__device__ __forceinline__ float tanh_fast(float x) { float r; asm("tanh.approx.f32 %0,%1;" : "=f"(r) : "f"(x)); return r; }
__device__ __forceinline__ uint32_t pack_bf16(float lo, float hi) { uint32_t r; asm("cvt.rn.bf16x2.f32 %0,%1,%2;" : "=r"(r) : "f"(hi), "f"(lo)); return r; }
__device__ __forceinline__ uint32_t half_bf16x2(uint32_t a) { uint32_t r; asm("mul.rn.bf16x2 %0,%1,%2;" : "=r"(r) : "r"(a), "r"(0x3F003F00u)); return r; }
__device__ __forceinline__ float bf_lo(uint32_t v) { return __uint_as_float(v << 16); }
__device__ __forceinline__ float bf_hi(uint32_t v) { return __uint_as_float(v & 0xFFFF0000u); }

__device__ __forceinline__ void cp16(uint32_t dst, const void* src) { asm volatile("cp.async.cg.shared.global [%0],[%1],16;" ::"r"(dst), "l"(src) : "memory"); }
__device__ __forceinline__ void cp16_z(uint32_t dst, const void* src, bool ignore) {
    asm volatile("{\n.reg .pred p;\nsetp.ne.b32 p,%2,0;\ncp.async.cg.shared.global [%0],[%1],16,p;\n}" ::"r"(dst), "l"(src), "r"((int)ignore) : "memory");
}
__device__ __forceinline__ void mbar_init(uint32_t bar, uint32_t cnt) { asm volatile("mbarrier.init.shared.b64 [%0],%1;" ::"r"(bar), "r"(cnt) : "memory"); }
__device__ __forceinline__ void mbar_arrive(uint32_t bar) { asm volatile("mbarrier.arrive.shared.b64 _,[%0];" ::"r"(bar) : "memory"); }
__device__ __forceinline__ void mbar_cp_arrive(uint32_t bar) { asm volatile("cp.async.mbarrier.arrive.noinc.shared.b64 [%0];" ::"r"(bar) : "memory"); }
__device__ __forceinline__ void mbar_wait(uint32_t bar, uint32_t parity) {
    uint32_t done;
    int spins = 0;
    do {
        asm volatile("{\n.reg .pred p;\nmbarrier.try_wait.parity.shared.b64 p,[%1],%2;\nselp.u32 %0,1,0,p;\n}" : "=r"(done) : "r"(bar), "r"(parity) : "memory");
    } while (!done && ++spins < (1 << 20));
}
__device__ __forceinline__ uint32_t lds32(uint32_t a) { uint32_t v; asm volatile("ld.shared.u32 %0,[%1];" : "=r"(v) : "r"(a) : "memory"); return v; }
__device__ __forceinline__ uint32_t lds16(uint32_t a) { uint32_t v; asm volatile("ld.shared.u16 %0,[%1];" : "=r"(v) : "r"(a) : "memory"); return v; }
__device__ __forceinline__ uint4 lds128(uint32_t a) { uint4 v; asm volatile("ld.shared.v4.u32 {%0,%1,%2,%3},[%4];" : "=r"(v.x), "=r"(v.y), "=r"(v.z), "=r"(v.w) : "r"(a) : "memory"); return v; }
__device__ __forceinline__ float4 lds128f(uint32_t a) { float4 v; asm volatile("ld.shared.v4.f32 {%0,%1,%2,%3},[%4];" : "=f"(v.x), "=f"(v.y), "=f"(v.z), "=f"(v.w) : "r"(a) : "memory"); return v; }
__device__ __forceinline__ void sts32(uint32_t a, uint32_t v) { asm volatile("st.shared.u32 [%0],%1;" ::"r"(a), "r"(v) : "memory"); }
__device__ __forceinline__ void sts16(uint32_t a, uint32_t v) { asm volatile("st.shared.u16 [%0],%1;" ::"r"(a), "h"((unsigned short)v) : "memory"); }
__device__ __forceinline__ void sts8(uint32_t a, uint32_t v) { asm volatile("st.shared.u8 [%0],%1;" ::"r"(a), "r"(v) : "memory"); }
__device__ __forceinline__ void sts64(uint32_t a, uint32_t x, uint32_t y) { asm volatile("st.shared.v2.u32 [%0],{%1,%2};" ::"r"(a), "r"(x), "r"(y) : "memory"); }
__device__ __forceinline__ void sts128(uint32_t a, uint4 v) { asm volatile("st.shared.v4.u32 [%0],{%1,%2,%3,%4};" ::"r"(a), "r"(v.x), "r"(v.y), "r"(v.z), "r"(v.w) : "memory"); }
__device__ __forceinline__ void sts128f(uint32_t a, float x, float y, float z, float w) { asm volatile("st.shared.v4.f32 [%0],{%1,%2,%3,%4};" ::"r"(a), "f"(x), "f"(y), "f"(z), "f"(w) : "memory"); }
__device__ __forceinline__ uint32_t atoms_inc(uint32_t a) { uint32_t r; asm volatile("atom.shared.add.u32 %0,[%1],1;" : "=r"(r) : "r"(a) : "memory"); return r; }
__device__ __forceinline__ void ldsm4t(uint32_t (&r)[4], uint32_t a) {
    asm volatile("ldmatrix.sync.aligned.m8n8.x4.trans.shared.b16 {%0,%1,%2,%3},[%4];" : "=r"(r[0]), "=r"(r[1]), "=r"(r[2]), "=r"(r[3]) : "r"(a) : "memory");
}
__device__ __forceinline__ uint4 ld_relaxed128(const void* p) {
    uint4 v;
    asm volatile("ld.relaxed.gpu.global.v4.u32 {%0,%1,%2,%3},[%4];" : "=r"(v.x), "=r"(v.y), "=r"(v.z), "=r"(v.w) : "l"(p) : "memory");
    return v;
}
__device__ __forceinline__ uint2 ld_relaxed64(const void* p) {
    uint2 v;
    asm volatile("ld.relaxed.gpu.global.v2.u32 {%0,%1},[%2];" : "=r"(v.x), "=r"(v.y) : "l"(p) : "memory");
    return v;
}
__device__ __forceinline__ void st_relaxed128(void* p, uint4 v) {
    asm volatile("st.relaxed.gpu.global.v4.u32 [%0],{%1,%2,%3,%4};" ::"l"(p), "r"(v.x), "r"(v.y), "r"(v.z), "r"(v.w) : "memory");
}
__device__ __forceinline__ void st_relaxed64(void* p, uint32_t x, uint32_t y) {
    asm volatile("st.relaxed.gpu.global.v2.u32 [%0],{%1,%2};" ::"l"(p), "r"(x), "r"(y) : "memory");
}

__device__ __forceinline__ void load_wfrag(uint32_t (&a)[4], uint32_t wbase, int ks, int warp4, int lane) {
    int mat = lane >> 3, r = lane & 7;
    int k = ks * 16 + (mat >> 1) * 8 + r;
    int chunk = warp4 * 2 + (mat & 1);
    ldsm4t(a, wbase + k * 128 + ((chunk ^ r) << 4));
}

constexpr int kSpinMax = 1 << 22;

__global__ void __launch_bounds__(kThreads, 1)
gatedgcn_kernel(const __nv_bfloat16* __restrict__ x, const __nv_bfloat16* __restrict__ eattr,
                const int* __restrict__ src, const int* __restrict__ dst,
                const __nv_bfloat16* __restrict__ wa, const __nv_bfloat16* __restrict__ wb,
                const __nv_bfloat16* __restrict__ wc, const __nv_bfloat16* __restrict__ wu,
                const __nv_bfloat16* __restrict__ wv, __nv_bfloat16* __restrict__ out) {
    extern __shared__ __align__(1024) unsigned char smem_raw[];
    const uint32_t sb = (uint32_t)__cvta_generic_to_shared(smem_raw);
    if (sb & 1023u) __trap();
    const int tid = threadIdx.x, lane = tid & 31;
    const int warp = __shfl_sync(~0u, tid >> 5, 0), wg = warp >> 2, warp4 = warp & 3;
    const int p = blockIdx.x;
    const int node0 = p * kNPC;
    const int nown = min(kNPC, kN - node0);
    STAMP(0);

    const int e0 = p * kCH;
    const int n4 = min(kCH, kE - e0) >> 2;
    int4 dv[3], sv[3];
#pragma unroll
    for (int k = 0; k < 3; k++) {
        int i = tid + k * kThreads;
        if (i < n4) dv[k] = __ldg(reinterpret_cast<const int4*>(dst + e0) + i);
    }
    const uint32_t tag = (__ldcg(&g_epoch[p]) + 1u) & 0x3FFFFu;
#pragma unroll
    for (int k = 0; k < 3; k++) {
        int i = tid + k * kThreads;
        if (i < n4) sv[k] = __ldg(reinterpret_cast<const int4*>(src + e0) + i);
    }
    {
        int k = tid >> 3, c = tid & 7;
        uint32_t off = k * 128 + ((c ^ (k & 7)) << 4);
        cp16(sb + SC_W + off, reinterpret_cast<const char*>(wa) + tid * 16);
        cp16(sb + SC_W + 8192 + off, reinterpret_cast<const char*>(wb) + tid * 16);
        cp16(sb + SC_W + 16384 + off, reinterpret_cast<const char*>(wv) + tid * 16);
        cp16(sb + SC_W + 24576 + off, reinterpret_cast<const char*>(wu) + tid * 16);
        if (tid < 128) cp16(sb + SC_W + 32768 + off, reinterpret_cast<const char*>(wc) + tid * 16);
        cp16_z(sb + SC_XOWN + off, reinterpret_cast<const char*>(x) + (size_t)node0 * 128 + (k < nown ? tid * 16 : 0), k >= nown);
        if (tid < 128) {
            int k2 = k + 64;
            cp16_z(sb + SC_XOWN + 8192 + off, reinterpret_cast<const char*>(x) + (size_t)node0 * 128 + (k2 < nown ? 8192 + tid * 16 : 0), k2 >= nown);
        }
        asm volatile("cp.async.commit_group;" ::: "memory");
    }
    if (tid < 132) sts32(sb + SC_HIST + tid * 4, 0);
    if (tid < 80) sts32(sb + SM_CNT + tid * 4, 0);
    if (tid < 16) sts32(sb + SM_VARS + tid * 4, 0);
    if (tid == 0) {
        for (int i = 0; i < kNWG * kStages; i++) {
            mbar_init(sb + SM_BAR + i * 8, 32);
            mbar_init(sb + SM_BAR + 96 + i * 8, 4);
        }
    }
    if (tid < 64) {
        int s = tid & 7;
        uint32_t v = (s & 1) ? 0x3F800000u : 0x00003F80u;
        int w = s >> 1;
        sts128(sb + SM_IDENT + tid * 16, make_uint4(w == 0 ? v : 0, w == 1 ? v : 0, w == 2 ? v : 0, w == 3 ? v : 0));
    }
    for (int i = tid; i < (SM_META - SM_LEID) / 16; i += kThreads) sts128(sb + SM_LEID + i * 16, make_uint4(~0u, ~0u, ~0u, ~0u));
    if (tid < 48) sts128(sb + SM_META + tid * 16, make_uint4(0x4C4C4C4Cu, 0x4C4C4C4Cu, 0x4C4C4C4Cu, 0x4C4C4C4Cu));
    __syncthreads();
    STAMP(1);
    if (tid == 0) g_epoch[p] = tag;

    uint32_t key[12];
#pragma unroll
    for (int k = 0; k < 3; k++) {
        if (tid + k * kThreads < n4) {
            int dd[4] = {dv[k].x, dv[k].y, dv[k].z, dv[k].w};
#pragma unroll
            for (int j = 0; j < 4; j++) {
                uint32_t d = (uint32_t)dd[j];
                uint32_t c = d / kNPC;
                uint32_t ln = d - c * kNPC;
                uint32_t r = atoms_inc(sb + SC_HIST + c * 4);
                key[k * 4 + j] = c | (ln << 8) | (r << 15);
            }
        }
    }
    if (tid == 32) {
        asm volatile("cp.async.bulk.prefetch.L2.global [%0],%1;" ::"l"(reinterpret_cast<const char*>(eattr) + (size_t)e0 * 32), "r"(n4 * 128) : "memory");
    }
    __syncthreads();
    STAMP(2);
    if (warp == 0) {
        uint32_t c[5], s = 0;
#pragma unroll
        for (int j = 0; j < 5; j++) {
            int b = lane * 5 + j;
            c[j] = b < kCTAs ? lds32(sb + SC_HIST + b * 4) : 0;
            s += (c[j] + 1) & ~1u;
        }
        uint32_t inc = s;
#pragma unroll
        for (int o = 1; o < 32; o <<= 1) {
            uint32_t t = __shfl_up_sync(~0u, inc, o);
            if (lane >= o) inc += t;
        }
        uint32_t run = inc - s;
#pragma unroll
        for (int j = 0; j < 5; j++) {
            int b = lane * 5 + j;
            if (b < kCTAs) {
                sts32(sb + SC_HIST + 1024 + b * 4, run);
                st_relaxed64(&g_hdr[b * kCTAs + p], run | (c[j] << 16), tag);
            }
            run += (c[j] + 1) & ~1u;
        }
        if (lane == 31) sts32(sb + SM_VARS + 0, inc);
    }
    __syncthreads();
    STAMP(3);
#pragma unroll
    for (int k = 0; k < 3; k++) {
        int i = tid + k * kThreads;
        if (i < n4) {
            int ss[4] = {sv[k].x, sv[k].y, sv[k].z, sv[k].w};
#pragma unroll
            for (int j = 0; j < 4; j++) {
                uint32_t ky = key[k * 4 + j];
                uint32_t pos = lds32(sb + SC_HIST + 1024 + (ky & 0xFF) * 4) + (ky >> 15);
                sts64(sb + SC_SORT + pos * 8, (uint32_t)(e0 + i * 4 + j) | (((ky >> 8) & 0x7F) << 20), (uint32_t)ss[j] | (tag << 14));
            }
        }
    }
    asm volatile("cp.async.wait_group 0;" ::: "memory");
    proxy_fence();
    __syncthreads();
    STAMP(4);
    {
        int tot2 = lds32(sb + SM_VARS + 0) >> 1;
        uint4* gdst = reinterpret_cast<uint4*>(g_rec + (size_t)p * kRecCap);
        for (int i = tid; i < tot2; i += kThreads) st_relaxed128(gdst + i, lds128(sb + SC_SORT + i * 16));
    }
    STAMP(5);

    {
        uint32_t wbase = sb + SC_W + ((wg & 2) ? 24576 : 0);
        uint32_t af[4][4];
#pragma unroll
        for (int ks = 0; ks < 4; ks++) load_wfrag(af[ks], wbase, ks, warp4, lane);
        float d[20];
        uint64_t dx = mkdesc(sb + SC_XOWN + (wg & 1) * 5120, 16, 1024, 1);
        wg_fence();
#pragma unroll
        for (int ks = 0; ks < 4; ks++) wgmma_n40(d, af[ks], dx + ks * 2, ks > 0);
        wg_commit();
        wg_wait<0>();
        fence_regs(d);
        float sc = (wg & 2) ? 1.0f : 0.5f;
        uint32_t tb = sb + ((wg & 2) ? SM_UTAB : SM_ATAB) + ((wg & 1) * 40 + (lane & 3) * 2) * 128 + (warp4 * 8 + (lane >> 2)) * 4;
#pragma unroll
        for (int j = 0; j < 5; j++) {
            sts32(tb + j * 1024, pack_bf16(d[4 * j] * sc, d[4 * j + 2] * sc));
            sts32(tb + j * 1024 + 128, pack_bf16(d[4 * j + 1] * sc, d[4 * j + 3] * sc));
        }
    }
    STAMP(6);

    const int sp0 = warp * 8 + min(warp, 4);
    const int nsp = warp < 4 ? 9 : 8;
    uint32_t hdr = 0;
    if (lane < nsp) {
        const unsigned long long* hp = &g_hdr[p * kCTAs + sp0 + lane];
        uint2 h = ld_relaxed64(hp);
        int spins = 0;
        while (h.y != tag) {
            if (++spins > kSpinMax) __trap();
            h = ld_relaxed64(hp);
        }
        hdr = h.x;
    }
    __syncwarp();
    STAMP(7);
    uint4 rv[9];
    uint32_t rk[9];
#pragma unroll
    for (int k = 0; k < 9; k++) {
        uint32_t h = __shfl_sync(~0u, hdr, k);
        uint32_t cnt = h >> 16;
        if (2 * lane < cnt) rv[k] = ld_relaxed128(g_rec + (size_t)(sp0 + k) * kRecCap + (h & 0xFFFF) + 2 * lane);
    }
#pragma unroll
    for (int k = 0; k < 9; k++) {
        uint32_t h = __shfl_sync(~0u, hdr, k);
        uint32_t cnt = h >> 16;
        uint32_t r0 = 0xFFFF, r1 = 0xFFFF;
        if (2 * lane < cnt) {
            bool two = 2 * lane + 1 < cnt;
            int spins = 0;
            while ((rv[k].y >> 14) != tag || (two && (rv[k].w >> 14) != tag)) {
                if (++spins > kSpinMax) __trap();
                rv[k] = ld_relaxed128(g_rec + (size_t)(sp0 + k) * kRecCap + (h & 0xFFFF) + 2 * lane);
            }
            r0 = min(atoms_inc(sb + SM_CNT + (rv[k].x >> 20) * 4), 0xFFFEu);
            if (two) r1 = min(atoms_inc(sb + SM_CNT + (rv[k].z >> 20) * 4), 0xFFFEu);
        }
        rk[k] = r0 | (r1 << 16);
        if (cnt > 64) {
            for (uint32_t i = 64 + lane; i < cnt; i += 32) {
                const unsigned long long* rp = g_rec + (size_t)(sp0 + k) * kRecCap + (h & 0xFFFF) + i;
                uint2 r = ld_relaxed64(rp);
                int spins = 0;
                while ((r.y >> 14) != tag) {
                    if (++spins > kSpinMax) __trap();
                    r = ld_relaxed64(rp);
                }
                uint32_t rr = atoms_inc(sb + SM_CNT + (r.x >> 20) * 4);
                uint32_t xi = atoms_inc(sb + SM_VARS + 4);
                if (xi < kExtraCap) {
                    sts32(sb + SC_EXTRA + xi * 12, r.x);
                    sts32(sb + SC_EXTRA + xi * 12 + 4, r.y);
                    sts32(sb + SC_EXTRA + xi * 12 + 8, rr);
                }
            }
        }
    }
    __syncthreads();
    STAMP(8);
    uint32_t L, invL, nOct;
    {
        uint32_t c[3], s = 0;
#pragma unroll
        for (int j = 0; j < 3; j++) {
            int b = lane * 3 + j;
            c[j] = b < kNPC ? (lds32(sb + SM_CNT + b * 4) + 7) >> 3 : 0;
            s += c[j];
        }
        uint32_t inc = s;
#pragma unroll
        for (int o = 1; o < 32; o <<= 1) {
            uint32_t t = __shfl_up_sync(~0u, inc, o);
            if (lane >= o) inc += t;
        }
        nOct = __shfl_sync(~0u, inc, 31);
        L = (nOct + kNWG * 8 - 1) / (kNWG * 8);
        if (L == 0) L = 1;
        invL = (65536u + L - 1) / L;
        if (warp == 0) {
            uint32_t run = inc - s;
#pragma unroll
            for (int j = 0; j < 3; j++) {
                int b = lane * 3 + j;
                if (b <= kNPC) sts32(sb + SC_OST + b * 4, run);
                run += c[j];
            }
        }
    }
    const uint32_t nExtra = __shfl_sync(~0u, lds32(sb + SM_VARS + 4), 0);
    const bool slow = (L > kLMax) || (nExtra > kExtraCap);
    __syncthreads();
    STAMP(9);

    if (slow) {
        for (int i = tid; i < 77 * 128; i += kThreads) sts32(sb + SM_ACC + i * 4, 0);
        __syncthreads();
        float* acc = reinterpret_cast<float*>(smem_raw + SM_ACC);
        const int ch = lane * 2;
        for (int sp = 0; sp < kCTAs; sp++) {
            uint32_t h = ld_relaxed64(&g_hdr[p * kCTAs + sp]).x;
            uint32_t cnt = h >> 16;
            for (uint32_t i = warp; i < cnt; i += 16) {
                uint2 r = ld_relaxed64(g_rec + (size_t)sp * kRecCap + (h & 0xFFFF) + i);
                uint32_t eid = r.x & 0xFFFFF, ln = r.x >> 20, s = r.y & 0x3FFF;
                uint32_t xv = __ldg(reinterpret_cast<const uint32_t*>(x) + s * 32 + lane);
                uint32_t ev = __ldg(reinterpret_cast<const uint32_t*>(eattr) + (size_t)eid * 8 + (lane & 7));
                float g0 = 0.f, g1 = 0.f, h0 = 0.f, h1 = 0.f;
                for (int k = 0; k < 64; k++) {
                    uint32_t xx = __shfl_sync(~0u, xv, k >> 1);
                    float xf = (k & 1) ? bf_hi(xx) : bf_lo(xx);
                    uint32_t off = k * 128 + (((ch >> 3) ^ (k & 7)) << 4) + (ch & 7) * 2;
                    uint32_t b = lds32(sb + SC_W + 8192 + off), v = lds32(sb + SC_W + 16384 + off);
                    g0 = fmaf(xf, bf_lo(b), g0); g1 = fmaf(xf, bf_hi(b), g1);
                    h0 = fmaf(xf, bf_lo(v), h0); h1 = fmaf(xf, bf_hi(v), h1);
                }
                for (int k = 0; k < 16; k++) {
                    uint32_t ee = __shfl_sync(~0u, ev, k >> 1);
                    float ef = (k & 1) ? bf_hi(ee) : bf_lo(ee);
                    uint32_t c = lds32(sb + SC_W + 32768 + k * 128 + (((ch >> 3) ^ (k & 7)) << 4) + (ch & 7) * 2);
                    g0 = fmaf(ef, bf_lo(c), g0); g1 = fmaf(ef, bf_hi(c), g1);
                }
                int row = (ch >> 4) * 8 + (ch & 7), hf = (ch >> 3) & 1;
                uint32_t a0 = lds32(sb + SM_ATAB + ln * 128 + row * 4), a1 = lds32(sb + SM_ATAB + ln * 128 + row * 4 + 4);
                float e0f = 1.0f + tanh_fast(0.5f * g0 + (hf ? bf_hi(a0) : bf_lo(a0)));
                float e1f = 1.0f + tanh_fast(0.5f * g1 + (hf ? bf_hi(a1) : bf_lo(a1)));
                float* ap = acc + ln * 128 + row * 4 + hf;
                atomicAdd(ap, e0f); atomicAdd(ap + 2, e0f * h0);
                atomicAdd(ap + 4, e1f); atomicAdd(ap + 6, e1f * h1);
            }
        }
        __syncthreads();
        for (int n = warp; n < nown; n += 16) {
            int row = (ch >> 4) * 8 + (ch & 7), hf = (ch >> 3) & 1;
            const float* ap = acc + n * 128 + row * 4 + hf;
            uint32_t u0 = lds32(sb + SM_UTAB + n * 128 + row * 4), u1 = lds32(sb + SM_UTAB + n * 128 + row * 4 + 4);
            uint32_t xv = __ldg(reinterpret_cast<const uint32_t*>(x) + (size_t)(node0 + n) * 32 + lane);
            float z0 = (hf ? bf_hi(u0) : bf_lo(u0)) + ap[2] / (ap[0] + 2e-6f);
            float z1 = (hf ? bf_hi(u1) : bf_lo(u1)) + ap[6] / (ap[4] + 2e-6f);
            reinterpret_cast<uint32_t*>(out)[(size_t)(node0 + n) * 32 + lane] = pack_bf16(bf_lo(xv) + fmaxf(z0, 0.f), bf_hi(xv) + fmaxf(z1, 0.f));
        }
        return;
    }

    auto place = [&](uint32_t w0, uint32_t w1, uint32_t rank) {
        uint32_t o = lds32(sb + SC_OST + (w0 >> 20) * 4) + (rank >> 3);
        uint32_t lam = (o * invL) >> 16;
        uint32_t t = o - lam * L;
        uint32_t tile = (lam >> 3) * kLMax + t;
        uint32_t col = (rank & 7) * 8 + (lam & 7);
        sts16(sb + SM_LSRC + (tile * 64 + col) * 2, w1 & 0x3FFF);
        sts32(sb + SM_LEID + (tile * 64 + (col & 15) * 4 + (col >> 4)) * 4, w0 & 0xFFFFF);
    };
#pragma unroll
    for (int k = 0; k < 9; k++) {
        uint32_t r0 = rk[k] & 0xFFFF, r1 = rk[k] >> 16;
        if (r0 != 0xFFFF) place(rv[k].x, rv[k].y, r0);
        if (r1 != 0xFFFF) place(rv[k].z, rv[k].w, r1);
    }
    if ((uint32_t)tid < nExtra) place(lds32(sb + SC_EXTRA + tid * 12), lds32(sb + SC_EXTRA + tid * 12 + 4), lds32(sb + SC_EXTRA + tid * 12 + 8));
    if (tid < 4 * kNPC) {
        int n = tid >> 2;
        uint32_t a = lds32(sb + SC_OST + n * 4), b = lds32(sb + SC_OST + n * 4 + 4);
        for (uint32_t o = a + (tid & 3); o < b; o += 4) {
            uint32_t lam = (o * invL) >> 16;
            uint32_t t = o - lam * L;
            sts8(sb + SM_META + ((lam >> 3) * kLMax + t) * 8 + (lam & 7), n);
        }
        if ((tid & 3) == 0) sts32(sb + SM_CNT + n * 4, a | (b << 16));
    }
    uint32_t fb[4][4], fv[4][4], fc[4];
    if (wg < kNWG) {
#pragma unroll
        for (int ks = 0; ks < 4; ks++) {
            load_wfrag(fb[ks], sb + SC_W + 8192, ks, warp4, lane);
            load_wfrag(fv[ks], sb + SC_W + 16384, ks, warp4, lane);
        }
        load_wfrag(fc, sb + SC_W + 32768, 0, warp4, lane);
#pragma unroll
        for (int j = 0; j < 4; j++) {
            fc[j] = half_bf16x2(fc[j]);
#pragma unroll
            for (int ks = 0; ks < 4; ks++) fb[ks][j] = half_bf16x2(fb[ks][j]);
        }
    }
    proxy_fence();
    __syncthreads();
    STAMP(10);

    if (wg == kNWG) {
        asm volatile("setmaxnreg.dec.sync.aligned.u32 40;");
        const int a = lane >> 3, c = lane & 7, hh = lane >> 1;
        const char* xg = reinterpret_cast<const char*>(x) + c * 16;
        const char* eg = reinterpret_cast<const char*>(eattr) + (lane & 1) * 16;
        const uint32_t xoff = a * 2048;
        const uint32_t eoff = 8192 + hh * 32 + (((lane & 1) ^ ((hh >> 2) & 1)) << 4);
        const uint32_t foff = 10240 + (hh + (lane & 1) * 32) * 16;
        const int ntile = kNWG * L;
        for (int k = warp4; k < ntile; k += 4) {
            uint32_t t = (uint32_t)k / kNWG, w = k - t * kNWG;
            uint32_t st = t % kStages;
            uint32_t bi = w * kStages + st;
            uint32_t tile = w * kLMax + t;
            uint4 s0 = lds128(sb + SM_LSRC + tile * 128 + a * 32);
            uint4 s1 = lds128(sb + SM_LSRC + tile * 128 + a * 32 + 16);
            uint4 ev = lds128(sb + SM_LEID + tile * 256 + hh * 16);
            if (t >= kStages) mbar_wait(sb + SM_BAR + 96 + bi * 8, ((t / kStages) - 1) & 1);
            uint32_t stage = sb + bi * kStageB;
            uint32_t sw[8] = {s0.x, s0.y, s0.z, s0.w, s1.x, s1.y, s1.z, s1.w};
#pragma unroll
            for (int i = 0; i < 16; i++) {
                uint32_t s = (i & 1) ? (sw[i >> 1] >> 16) : (sw[i >> 1] & 0xFFFF);
                cp16_z(stage + xoff + i * 128 + ((c ^ (i & 7)) << 4), xg + (size_t)s * 128, s == 0xFFFF);
            }
            uint32_t ee[4] = {ev.x, ev.y, ev.z, ev.w};
#pragma unroll
            for (int i = 0; i < 4; i++) cp16_z(stage + eoff + i * 512, eg + (size_t)(ee[i] & 0xFFFFF) * 32, ee[i] == ~0u);
            uint32_t f0 = (lane & 1) ? ee[2] : ee[0], f1 = (lane & 1) ? ee[3] : ee[1];
            cp16_z(stage + foff, g_flag, f0 != ~0u);
            cp16_z(stage + foff + 256, g_flag, f1 != ~0u);
            mbar_cp_arrive(sb + SM_BAR + bi * 8);
        }
        asm volatile("cp.async.wait_all;" ::: "memory");
    } else {
        asm volatile("setmaxnreg.inc.sync.aligned.u32 152;");
        const int q = lane & 3;
        const int row = warp4 * 8 + (lane >> 2);
        const uint32_t atab = sb + SM_ATAB + row * 4;
        const uint32_t acct = sb + SM_ACC + row * 16;
        const uint32_t mtab = sb + SM_META + wg * kLMax * 8 + q * 2;
        uint32_t fa[4];
        fa[0] = fa[1] = (q == 0) ? 0x0000FF00u : 0u;
        uint32_t cur = lds16(mtab);
        {
            uint32_t a0 = lds32(atab + (cur & 0xFF) * 128), a1 = lds32(atab + (cur >> 8) * 128);
            fa[2] = __byte_perm(a0, a1, 0x5410);
            fa[3] = __byte_perm(a0, a1, 0x7632);
        }
        float num[4] = {0.f, 0.f, 0.f, 0.f}, den[4] = {0.f, 0.f, 0.f, 0.f};
        float g[32], h[32];
        uint32_t st = 0, ph = 0;
        for (uint32_t t = 0; t < L; t++) {
            const uint32_t bi = wg * kStages + st;
            const uint32_t stage = sb + bi * kStageB;
            const uint64_t dx = mkdesc(stage, 16, 1024, 1);
            const uint64_t de = mkdesc(stage + 8192, 16, 256, 3);
            const uint64_t df = mkdesc(stage + 10240, SM_IDENT - 10240 - bi * kStageB, 128, 0);
            mbar_wait(sb + SM_BAR + bi * 8, ph);
            proxy_fence();
            wg_fence();
            wgmma_n64(g, fc, de, 0);
            wgmma_n64(g, fa, df, 1);
#pragma unroll
            for (int k = 0; k < 4; k++) wgmma_n64(g, fb[k], dx + k * 2, 1);
            wg_commit();
#pragma unroll
            for (int k = 0; k < 4; k++) wgmma_n64(h, fv[k], dx + k * 2, k > 0);
            wg_commit();
            uint32_t nxt = lds16(mtab + (t + 1) * 8);
            wg_wait<1>();
            fence_regs(g);
#pragma unroll
            for (int i = 0; i < 32; i++) {
                g[i] = 1.0f + tanh_fast(g[i]);
                den[i & 3] += g[i];
            }
            wg_wait<0>();
            fence_regs(h);
            if (lane == 0) mbar_arrive(sb + SM_BAR + 96 + bi * 8);
#pragma unroll
            for (int i = 0; i < 32; i++) num[i & 3] = fmaf(g[i], h[i], num[i & 3]);
            if (t + 1 < L) {
                uint32_t diff = cur ^ nxt;
                if (diff & 0xFF) {
                    sts128f(acct + (cur & 0xFF) * 512, den[0], den[2], num[0], num[2]);
                    den[0] = den[2] = num[0] = num[2] = 0.f;
                    uint32_t av = lds32(atab + (nxt & 0xFF) * 128);
                    fa[2] = __byte_perm(fa[2], av, 0x3254);
                    fa[3] = __byte_perm(fa[3], av, 0x3276);
                }
                if (diff >> 8) {
                    sts128f(acct + (cur >> 8) * 512, den[1], den[3], num[1], num[3]);
                    den[1] = den[3] = num[1] = num[3] = 0.f;
                    uint32_t av = lds32(atab + (nxt >> 8) * 128);
                    fa[2] = __byte_perm(fa[2], av, 0x5410);
                    fa[3] = __byte_perm(fa[3], av, 0x7610);
                }
                cur = nxt;
            }
            if (++st == kStages) { st = 0; ph ^= 1; }
        }
        STAMP(11);
        {
            uint32_t tb = sb + SM_LEID + wg * kLMax * 256 + q * 1024 + row * 16;
            sts128f(tb, den[0], den[2], num[0], num[2]);
            sts128f(tb + 512, den[1], den[3], num[1], num[3]);
        }
        uint32_t xv[7];
#pragma unroll
        for (int i = 0; i < 7; i++) {
            int n = warp + i * 12;
            if (n < nown) xv[i] = __ldg(reinterpret_cast<const uint32_t*>(x) + (size_t)(node0 + n) * 32 + lane);
        }
        asm volatile("bar.sync 1, 384;" ::: "memory");
        const int ch = lane * 2;
        const int r2 = (ch >> 4) * 8 + (ch & 7), hf = (ch >> 3) & 1;
#pragma unroll
        for (int i = 0; i < 7; i++) {
            int n = warp + i * 12;
            if (n < nown) {
                uint32_t ab = lds32(sb + SM_CNT + n * 4);
                uint32_t a = ab & 0xFFFF, b = ab >> 16;
                uint32_t la = (a * invL) >> 16, lb = (b * invL) >> 16;
                float d0 = 0.f, d1 = 0.f, n0 = 0.f, n1 = 0.f;
                if (a < b && lb * L != b) {
                    float4 u = lds128f(sb + SM_ACC + n * 512 + r2 * 16), v = lds128f(sb + SM_ACC + n * 512 + r2 * 16 + 16);
                    d0 = hf ? u.y : u.x; n0 = hf ? u.w : u.z;
                    d1 = hf ? v.y : v.x; n1 = hf ? v.w : v.z;
                }
                for (uint32_t l = la; l < lb; l++) {
                    uint32_t tb = sb + SM_LEID + (l >> 3) * kLMax * 256 + (l & 7) * 512 + r2 * 16;
                    float4 u = lds128f(tb), v = lds128f(tb + 16);
                    d0 += hf ? u.y : u.x; n0 += hf ? u.w : u.z;
                    d1 += hf ? v.y : v.x; n1 += hf ? v.w : v.z;
                }
                uint32_t u0 = lds32(sb + SM_UTAB + n * 128 + r2 * 4), u1 = lds32(sb + SM_UTAB + n * 128 + r2 * 4 + 4);
                float z0 = (hf ? bf_hi(u0) : bf_lo(u0)) + __fdividef(n0, d0 + 2e-6f);
                float z1 = (hf ? bf_hi(u1) : bf_lo(u1)) + __fdividef(n1, d1 + 2e-6f);
                reinterpret_cast<uint32_t*>(out)[(size_t)(node0 + n) * 32 + lane] =
                    pack_bf16(bf_lo(xv[i]) + fmaxf(z0, 0.f), bf_hi(xv[i]) + fmaxf(z1, 0.f));
            }
        }
        STAMP(12);
    }
}

}

extern "C" void kernel_launch(void* const* d_in, const int* in_sizes, int n_in, void* d_out, int out_size) {
    const __nv_bfloat16* x = (const __nv_bfloat16*)d_in[0];
    const __nv_bfloat16* eattr = (const __nv_bfloat16*)d_in[1];
    const int* src = (const int*)d_in[2];
    const int* dst = (const int*)d_in[3];
    const __nv_bfloat16* wa = (const __nv_bfloat16*)d_in[4];
    const __nv_bfloat16* wb = (const __nv_bfloat16*)d_in[5];
    const __nv_bfloat16* wc = (const __nv_bfloat16*)d_in[6];
    const __nv_bfloat16* wu = (const __nv_bfloat16*)d_in[7];
    const __nv_bfloat16* wv = (const __nv_bfloat16*)d_in[8];
    static bool init = false;
    if (!init) {
        cudaFuncSetAttribute(gatedgcn_kernel, cudaFuncAttributeMaxDynamicSharedMemorySize, SM_TOTAL);
        init = true;
    }
    gatedgcn_kernel<<<kCTAs, kThreads, SM_TOTAL>>>(x, eattr, src, dst, wa, wb, wc, wu, wv, (__nv_bfloat16*)d_out);
}
```

```cpp
#include <cuda_runtime.h>
#include <cuda_bf16.h>
#include <stdint.h>

namespace {

constexpr int kN = 10000;
constexpr int kE = 640000;
constexpr int kCTAs = 132;
constexpr int kNPC = 76;
constexpr int kCH = 4852;
constexpr int kCap = 64;
constexpr int kThreads = 512;
constexpr int kNWG = 3;
constexpr int kStages = 4;
constexpr int kTMax = 96;
constexpr int kStageB = 10240;
constexpr int kRowCap = 112;
constexpr int kRowB = 976;
constexpr int kEidOff = 512;
constexpr int kTabB = 144;

constexpr int SM_STAGE = 0;
constexpr int SM_FLAG = SM_STAGE + kNWG * kStages * kStageB;
constexpr int SM_IDENT = SM_FLAG + kNWG * kStages * 512;
constexpr int SM_ROW = SM_IDENT + 1024;
constexpr int SM_HEAD = SM_ROW + 76 * kRowB + 544;
constexpr int SM_ATAB = SM_HEAD + 24 * 512;
constexpr int SM_OTAB = SM_ATAB + 78 * kTabB;
constexpr int SM_BAR = SM_OTAB + kTMax * 16;
constexpr int SM_HS = SM_BAR + 192;
constexpr int SM_OEND = SM_HS + 528;
constexpr int SM_NINFO = SM_OEND + 320;
constexpr int SM_LFIRST = SM_NINFO + 320;
constexpr int SM_LOW = SM_LFIRST + 96;
constexpr int SM_DEG = SM_LOW + 64;
constexpr int SM_VARS = SM_DEG + 80;
constexpr int SM_PATCH = SM_VARS + 32;
constexpr int SM_TOTAL = SM_PATCH + 512;
constexpr int SC_WA = 0;
constexpr int SC_WU = 8192;
constexpr int SC_WB = 16384;
constexpr int SC_WV = 24576;
constexpr int SC_WC = 32768;
constexpr int SC_XOWN = 34816;
constexpr int SC_SORT = SC_XOWN + 10240;
constexpr int SC_CNT = SM_HEAD + 80 * kTabB;
constexpr int SC_ACC = SC_SORT + kCTAs * kCap * 4;
constexpr int SC_UTAB = SM_HEAD;
static_assert(SC_ACC + 76 * 512 <= SM_FLAG && SM_HEAD % 16 == 0 && SM_BAR % 8 == 0 && SM_PATCH % 16 == 0, "scratch");
constexpr uint32_t kRB = 86, kRE = 4853, kRS = 10030, kRD = 111697813u;
constexpr uint32_t enc_const(uint32_t ln) { return ln * kRE * kRS + (uint32_t)(((unsigned long long)(ln * kRE * kRS) * kRD) >> 32) + 1; }
constexpr uint32_t kPad0 = enc_const(76), kPadStep = enc_const(77) - enc_const(76) + 1;
constexpr uint32_t kCntBase = (enc_const(85) + 63) / 64 * 64 + 1;
static_assert(SM_TOTAL <= 232448, "smem");

struct Scratch {
    unsigned int rec[kCTAs * kCTAs * kCap];
    uint2 ovf[kCTAs * kCH];
};
__device__ __align__(128) Scratch g_scratch;

__device__ __forceinline__ void wg_fence() { asm volatile("wgmma.fence.sync.aligned;" ::: "memory"); }
__device__ __forceinline__ void wg_commit() { asm volatile("wgmma.commit_group.sync.aligned;" ::: "memory"); }
template <int N> __device__ __forceinline__ void wg_wait() { asm volatile("wgmma.wait_group.sync.aligned %0;" ::"n"(N) : "memory"); }
__device__ __forceinline__ void proxy_fence() { asm volatile("fence.proxy.async.shared::cta;" ::: "memory"); }

__device__ __forceinline__ void wgmma_n64(float (&d)[32], const uint32_t (&a)[4], uint64_t desc, int scale_d) {
    asm volatile(
        "{\n.reg .pred p;\nsetp.ne.b32 p, %37, 0;\n"
        "wgmma.mma_async.sync.aligned.m64n64k16.f32.bf16.bf16 "
        "{%0,%1,%2,%3,%4,%5,%6,%7,%8,%9,%10,%11,%12,%13,%14,%15,%16,%17,%18,%19,%20,%21,%22,%23,%24,%25,%26,%27,%28,%29,%30,%31},"
        "{%32,%33,%34,%35}, %36, p, 1, 1, 0;\n}\n"
        : "+f"(d[0]), "+f"(d[1]), "+f"(d[2]), "+f"(d[3]), "+f"(d[4]), "+f"(d[5]), "+f"(d[6]), "+f"(d[7]),
          "+f"(d[8]), "+f"(d[9]), "+f"(d[10]), "+f"(d[11]), "+f"(d[12]), "+f"(d[13]), "+f"(d[14]), "+f"(d[15]),
          "+f"(d[16]), "+f"(d[17]), "+f"(d[18]), "+f"(d[19]), "+f"(d[20]), "+f"(d[21]), "+f"(d[22]), "+f"(d[23]),
          "+f"(d[24]), "+f"(d[25]), "+f"(d[26]), "+f"(d[27]), "+f"(d[28]), "+f"(d[29]), "+f"(d[30]), "+f"(d[31])
        : "r"(a[0]), "r"(a[1]), "r"(a[2]), "r"(a[3]), "l"(desc), "r"(scale_d));
}
__device__ __forceinline__ void wgmma_n40(float (&d)[20], const uint32_t (&a)[4], uint64_t desc, int scale_d) {
    asm volatile(
        "{\n.reg .pred p;\nsetp.ne.b32 p, %25, 0;\n"
        "wgmma.mma_async.sync.aligned.m64n40k16.f32.bf16.bf16 "
        "{%0,%1,%2,%3,%4,%5,%6,%7,%8,%9,%10,%11,%12,%13,%14,%15,%16,%17,%18,%19},"
        "{%20,%21,%22,%23}, %24, p, 1, 1, 0;\n}\n"
        : "+f"(d[0]), "+f"(d[1]), "+f"(d[2]), "+f"(d[3]), "+f"(d[4]), "+f"(d[5]), "+f"(d[6]), "+f"(d[7]),
          "+f"(d[8]), "+f"(d[9]), "+f"(d[10]), "+f"(d[11]), "+f"(d[12]), "+f"(d[13]), "+f"(d[14]), "+f"(d[15]),
          "+f"(d[16]), "+f"(d[17]), "+f"(d[18]), "+f"(d[19])
        : "r"(a[0]), "r"(a[1]), "r"(a[2]), "r"(a[3]), "l"(desc), "r"(scale_d));
}
__device__ __forceinline__ void mma16816(float (&d)[4], const uint32_t (&a)[4], uint32_t b0, uint32_t b1) {
    asm volatile("mma.sync.aligned.m16n8k16.row.col.f32.bf16.bf16.f32 {%0,%1,%2,%3},{%4,%5,%6,%7},{%8,%9},{%0,%1,%2,%3};"
                 : "+f"(d[0]), "+f"(d[1]), "+f"(d[2]), "+f"(d[3]) : "r"(a[0]), "r"(a[1]), "r"(a[2]), "r"(a[3]), "r"(b0), "r"(b1));
}
template <int R> __device__ __forceinline__ void fence_regs(float (&d)[R]) {
#pragma unroll
    for (int i = 0; i < R; i++) asm volatile("" : "+f"(d[i])::"memory");
}
__device__ __forceinline__ uint64_t mkdesc(uint32_t addr, uint32_t lbo, uint32_t sbo, uint32_t swz) {
    return (uint64_t)((addr & 0x3FFFF) >> 4) | ((uint64_t)(lbo >> 4) << 16) | ((uint64_t)(sbo >> 4) << 32) | ((uint64_t)swz << 62);
}
__device__ __forceinline__ float tanh_fast(float x) { float r; asm("tanh.approx.f32 %0,%1;" : "=f"(r) : "f"(x)); return r; }
__device__ __forceinline__ float ex2_fast(float x) { float r; asm("ex2.approx.ftz.f32 %0,%1;" : "=f"(r) : "f"(x)); return r; }
__device__ __forceinline__ float rcp_fast(float x) { float r; asm("rcp.approx.ftz.f32 %0,%1;" : "=f"(r) : "f"(x)); return r; }
__device__ __forceinline__ uint32_t pack_bf16(float lo, float hi) { uint32_t r; asm("cvt.rn.bf16x2.f32 %0,%1,%2;" : "=r"(r) : "f"(hi), "f"(lo)); return r; }
__device__ __forceinline__ uint32_t half_bf16x2(uint32_t a) { uint32_t r; asm("mul.rn.bf16x2 %0,%1,%2;" : "=r"(r) : "r"(a), "r"(0x3F003F00u)); return r; }
__device__ __forceinline__ float bf_lo(uint32_t v) { return __uint_as_float(v << 16); }
__device__ __forceinline__ float bf_hi(uint32_t v) { return __uint_as_float(v & 0xFFFF0000u); }

__device__ __forceinline__ void cp16(uint32_t dst, const void* src) { asm volatile("cp.async.cg.shared.global [%0],[%1],16;" ::"r"(dst), "l"(src) : "memory"); }
__device__ __forceinline__ void cp16_z(uint32_t dst, const void* src, bool ignore) {
    asm volatile("{\n.reg .pred p;\nsetp.ne.b32 p,%2,0;\ncp.async.cg.shared.global [%0],[%1],16,p;\n}" ::"r"(dst), "l"(src), "r"((int)ignore) : "memory");
}
__device__ __forceinline__ void mbar_init(uint32_t bar, uint32_t cnt) { asm volatile("mbarrier.init.shared.b64 [%0],%1;" ::"r"(bar), "r"(cnt) : "memory"); }
__device__ __forceinline__ void mbar_cp_arrive(uint32_t bar) { asm volatile("cp.async.mbarrier.arrive.noinc.shared.b64 [%0];" ::"r"(bar) : "memory"); }
__device__ __forceinline__ void mbar_wait(uint32_t bar, uint32_t parity) {
    asm volatile(
        "{\n.reg .pred p;\n.reg .u32 c;\n"
        "mbarrier.try_wait.parity.shared.b64 p,[%0],%1;\n@p bra DONE;\n"
        "mov.u32 c,0;\n"
        "LOOP:\n"
        "mbarrier.try_wait.parity.shared.b64 p,[%0],%1;\n@p bra DONE;\n"
        "mbarrier.try_wait.parity.shared.b64 p,[%0],%1;\n@p bra DONE;\n"
        "mbarrier.try_wait.parity.shared.b64 p,[%0],%1;\n@p bra DONE;\n"
        "mbarrier.try_wait.parity.shared.b64 p,[%0],%1;\n@p bra DONE;\n"
        "add.u32 c,c,1;\nsetp.lt.u32 p,c,262144;\n@p bra LOOP;\n"
        "DONE:\n}" ::"r"(bar), "r"(parity) : "memory");
}
__device__ __forceinline__ uint32_t mbar_test(uint32_t bar, uint32_t parity) {
    uint32_t done;
    asm volatile("{\n.reg .pred p;\nmbarrier.test_wait.parity.shared.b64 p,[%1],%2;\nselp.u32 %0,1,0,p;\n}" : "=r"(done) : "r"(bar), "r"(parity) : "memory");
    return done;
}
__device__ __forceinline__ uint32_t lds32(uint32_t a) { uint32_t v; asm volatile("ld.shared.u32 %0,[%1];" : "=r"(v) : "r"(a) : "memory"); return v; }
__device__ __forceinline__ uint32_t lds16(uint32_t a) { uint32_t v; asm volatile("ld.shared.u16 %0,[%1];" : "=r"(v) : "r"(a) : "memory"); return v; }
__device__ __forceinline__ uint4 lds128(uint32_t a) { uint4 v; asm volatile("ld.shared.v4.u32 {%0,%1,%2,%3},[%4];" : "=r"(v.x), "=r"(v.y), "=r"(v.z), "=r"(v.w) : "r"(a) : "memory"); return v; }
__device__ __forceinline__ void sts32(uint32_t a, uint32_t v) { asm volatile("st.shared.u32 [%0],%1;" ::"r"(a), "r"(v) : "memory"); }
__device__ __forceinline__ void sts128(uint32_t a, uint4 v) { asm volatile("st.shared.v4.u32 [%0],{%1,%2,%3,%4};" ::"r"(a), "r"(v.x), "r"(v.y), "r"(v.z), "r"(v.w) : "memory"); }
__device__ __forceinline__ void sts128f(uint32_t a, float x, float y, float z, float w) { asm volatile("st.shared.v4.f32 [%0],{%1,%2,%3,%4};" ::"r"(a), "f"(x), "f"(y), "f"(z), "f"(w) : "memory"); }
__device__ __forceinline__ uint32_t atoms_inc(uint32_t a) { uint32_t r; asm volatile("atom.shared.add.u32 %0,[%1],1;" : "=r"(r) : "r"(a) : "memory"); return r; }
__device__ __forceinline__ void sts32_if(uint32_t a, uint32_t x, bool pr) {
    asm volatile("{\n.reg .pred p;\nsetp.ne.b32 p,%2,0;\n@p st.shared.u32 [%0],%1;\n}" ::"r"(a), "r"(x), "r"((int)pr) : "memory");
}
__device__ __forceinline__ void sts32x2_if(uint32_t a, uint32_t x, uint32_t y, bool pr) {
    asm volatile("{\n.reg .pred p;\nsetp.ne.b32 p,%3,0;\n@p st.shared.u32 [%0],%1;\n@p st.shared.u32 [%0+512],%2;\n}" ::"r"(a), "r"(x), "r"(y), "r"((int)pr) : "memory");
}
__device__ __forceinline__ void ld_relaxed128_if(uint4& v, const void* p, bool pr) {
    asm volatile("{\n.reg .pred p;\nsetp.ne.b32 p,%5,0;\n@p ld.relaxed.gpu.global.v4.u32 {%0,%1,%2,%3},[%4];\n}"
                 : "+r"(v.x), "+r"(v.y), "+r"(v.z), "+r"(v.w) : "l"(p), "r"((int)pr) : "memory");
}
#define ADDRGEN "mad.wide.s32 a,%2,%3,%1;"
template <int SCALE> __device__ __forceinline__ void cp16_idx(uint32_t dst, uint64_t base, uint32_t idx) {
    asm volatile("{\n.reg .u64 a;\n" ADDRGEN "\ncp.async.cg.shared.global [%0],[a],16;\n}" ::"r"(dst), "l"(base), "r"(idx), "n"(SCALE) : "memory");
}
template <int SCALE> __device__ __forceinline__ void cp16_idx_z(uint32_t dst, uint64_t base, uint32_t idx) {
    asm volatile("{\n.reg .pred p;\n.reg .u64 a;\nsetp.lt.s32 p,%2,0;\n" ADDRGEN "\ncp.async.cg.shared.global [%0],[a],16,p;\n}"
                 ::"r"(dst), "l"(base), "r"(idx), "n"(SCALE) : "memory");
}
__device__ __forceinline__ void ldsm4t(uint32_t (&r)[4], uint32_t a) {
    asm volatile("ldmatrix.sync.aligned.m8n8.x4.trans.shared.b16 {%0,%1,%2,%3},[%4];" : "=r"(r[0]), "=r"(r[1]), "=r"(r[2]), "=r"(r[3]) : "r"(a) : "memory");
}
__device__ __forceinline__ uint2 ld_relaxed64(const void* p) {
    uint2 v;
    asm volatile("ld.relaxed.gpu.global.v2.u32 {%0,%1},[%2];" : "=r"(v.x), "=r"(v.y) : "l"(p) : "memory");
    return v;
}
__device__ __forceinline__ uint32_t ld_relaxed32(const void* p) {
    uint32_t v;
    asm volatile("ld.relaxed.gpu.global.u32 %0,[%1];" : "=r"(v) : "l"(p) : "memory");
    return v;
}
__device__ __forceinline__ void st_relaxed64(void* p, uint32_t x, uint32_t y) {
    asm volatile("st.relaxed.gpu.global.v2.u32 [%0],{%1,%2};" ::"l"(p), "r"(x), "r"(y) : "memory");
}

__device__ __forceinline__ void load_wfrag(uint32_t (&a)[4], uint32_t wbase, int ks, int warp4, int lane) {
    int mat = lane >> 3, r = lane & 7;
    int k = ks * 16 + (mat >> 1) * 8 + r;
    int chunk = warp4 * 2 + (mat & 1);
    ldsm4t(a, wbase + k * 128 + ((chunk ^ r) << 4));
}

__device__ __forceinline__ void clear_slots(Scratch* scr, int p, int first, int step, int lane) {
    char* base = reinterpret_cast<char*>(scr->rec) + ((size_t)(2 * first + (lane >> 4)) * kCTAs + p) * (kCap * 4) + (lane & 15) * 16;
#pragma unroll 1
    for (int pr = first; pr < kCTAs / 2; pr += step, base += (size_t)step * (2 * kCTAs * kCap * 4))
        asm volatile("st.global.v4.u32 [%0],{%1,%1,%1,%1};" ::"l"(base), "r"(0) : "memory");
}
__device__ __forceinline__ void clear_overflow(Scratch* scr, uint32_t sb, int p, int w, int nw, int lane) {
#pragma unroll 1
    for (int s0 = w * 32; s0 < kCTAs; s0 += nw * 32) {
        const uint32_t lim = s0 + lane < kCTAs ? lds32(sb + SM_HS + (s0 + lane) * 4) >> 16 : 0;
#pragma unroll 1
        for (uint32_t m = __ballot_sync(~0u, lim != 0); m; m &= m - 1) {
            const int sp = s0 + __ffs(m) - 1;
            const uint32_t n = __shfl_sync(~0u, lim, __ffs(m) - 1);
#pragma unroll 1
            for (uint32_t i = lane; i < n; i += 32)
                if (ld_relaxed64(&scr->ovf[sp * kCH + i]).y == (uint32_t)p + 1) st_relaxed64(&scr->ovf[sp * kCH + i], 0, 0);
        }
    }
}

__device__ __forceinline__ void ld_idx3(uint4 (&v)[3], const int* p, bool third) {
    asm volatile(
        "{\n.reg .pred p;\nsetp.ne.b32 p,%13,0;\n"
        "ld.relaxed.gpu.global.v4.u32 {%0,%1,%2,%3},[%12];\n"
        "ld.relaxed.gpu.global.v4.u32 {%4,%5,%6,%7},[%12+8192];\n"
        "@p ld.relaxed.gpu.global.v4.u32 {%8,%9,%10,%11},[%12+16384];\n}"
        : "=r"(v[0].x), "=r"(v[0].y), "=r"(v[0].z), "=r"(v[0].w), "=r"(v[1].x), "=r"(v[1].y), "=r"(v[1].z), "=r"(v[1].w),
          "+r"(v[2].x), "+r"(v[2].y), "+r"(v[2].z), "+r"(v[2].w)
        : "l"(p), "r"((int)third)
        : "memory");
}

__device__ __forceinline__ uint32_t finish_pair(const float4& v, uint32_t u, uint32_t xv, int lane) {
    const float a0 = v.z * rcp_fast(v.x + 2e-6f), a1 = v.w * rcp_fast(v.y + 2e-6f);
    const float rcv = __shfl_xor_sync(~0u, (lane & 1) ? a0 : a1, 1);
    const float z0 = bf_lo(u) + ((lane & 1) ? rcv : a0);
    const float z1 = bf_hi(u) + ((lane & 1) ? a1 : rcv);
    return pack_bf16(bf_lo(xv) + fmaxf(z0, 0.f), bf_hi(xv) + fmaxf(z1, 0.f));
}
__device__ __forceinline__ void ld_frag(uint32_t (&a)[4], uint32_t wf, int i) {
    const uint4 v = lds128(wf + (i / 3) * (kStages * kStageB) + (i % 3) * 512);
    a[0] = v.x; a[1] = v.y; a[2] = v.z; a[3] = v.w;
}
template <class Gate>
__device__ __forceinline__ void exact_node(Gate gate, uint32_t sb, const int* src, const __nv_bfloat16* x, const __nv_bfloat16* eattr, int part,
                                           int lane, uint32_t n, uint32_t dest) {
    uint32_t cnt;
    asm volatile("ld.shared.u8 %0,[%1];" : "=r"(cnt) : "r"(sb + SM_DEG + n) : "memory");
    const uint32_t rowb = sb + SM_ROW + n * kRowB;
#pragma unroll 1
    for (uint32_t t0 = part * 8; t0 < max(cnt, 32u); t0 += 96) {
        uint32_t eid[3], sid[3], be[3][2], bx[3][8];
#pragma unroll
        for (int i = 0; i < 3; i++) eid[i] = lds32(rowb + kEidOff + min(t0 + 32 * i + (lane >> 2), cnt - 1) * 4);
#pragma unroll
        for (int i = 0; i < 3; i++) asm volatile("ld.global.u32 %0,[%1];" : "=r"(sid[i]) : "l"(src + eid[i]) : "memory");
#pragma unroll
        for (int i = 0; i < 3; i++)
            asm volatile("ld.global.u32 %0,[%2];\nld.global.u32 %1,[%2+16];" : "=r"(be[i][0]), "=r"(be[i][1]) : "l"(eattr + (size_t)eid[i] * 16 + (lane & 3) * 2) : "memory");
#pragma unroll
        for (int i = 0; i < 3; i++)
            asm volatile("ld.global.u32 %0,[%8];\nld.global.u32 %2,[%8+32];\nld.global.u32 %4,[%8+64];\nld.global.u32 %6,[%8+96];\n"
                         "ld.global.u32 %1,[%8+16];\nld.global.u32 %3,[%8+48];\nld.global.u32 %5,[%8+80];\nld.global.u32 %7,[%8+112];"
                         : "=r"(bx[i][0]), "=r"(bx[i][1]), "=r"(bx[i][2]), "=r"(bx[i][3]), "=r"(bx[i][4]), "=r"(bx[i][5]), "=r"(bx[i][6]), "=r"(bx[i][7])
                         : "l"(x + sid[i] * 64 + (lane & 3) * 2) : "memory");
#pragma unroll 1
        for (uint32_t rows = gate(); rows;) {
            const uint32_t grp = (__ffs(rows) - 1) >> 3;
            rows &= ~(0xFFu << (grp * 8));
            const uint32_t bias = lds32(sb + SM_ATAB + n * kTabB + (grp * 8 + (lane >> 2)) * 4);
            const uint32_t wf = sb + kStageB + grp * 1536 + lane * 16;
            uint32_t fw[4];
            float cg[3][4], s4[4] = {0.f, 0.f, 0.f, 0.f};
            int lim;
            asm volatile("ld.shared.u8 %0,[%1];" : "=r"(lim) : "r"(sb + SM_DEG + n) : "memory");
            lim -= t0 + (lane & 3) * 2;
            ld_frag(fw, wf, 8);
#pragma unroll
            for (int i = 0; i < 3; i++) {
                cg[i][0] = cg[i][1] = bf_lo(bias);
                cg[i][2] = cg[i][3] = bf_hi(bias);
                mma16816(cg[i], fw, be[i][0], be[i][1]);
            }
#pragma unroll
            for (int ks = 0; ks < 4; ks++) {
                ld_frag(fw, wf, ks);
#pragma unroll
                for (int i = 0; i < 3; i++) mma16816(cg[i], fw, bx[i][2 * ks], bx[i][2 * ks + 1]);
            }
#pragma unroll
            for (int i = 0; i < 3; i++) {
                float chv[4] = {0.f, 0.f, 0.f, 0.f};
#pragma unroll
                for (int ks = 0; ks < 4; ks++) {
                    ld_frag(fw, wf, 4 + ks);
                    mma16816(chv, fw, bx[i][2 * ks], bx[i][2 * ks + 1]);
                }
#pragma unroll
                for (int c = 0; c < 4; c++) {
                    float r = rcp_fast(fmaf(ex2_fast(cg[i][c] * -2.885390082f), 0.5f, 0.5f));
                    if (32 * i + (c & 1) >= lim) r = 0.f;
                    s4[c >> 1] += r;
                    s4[2 + (c >> 1)] = fmaf(r, chv[c], s4[2 + (c >> 1)]);
                }
            }
#pragma unroll
            for (int c = 0; c < 4; c++) {
                s4[c] += __shfl_xor_sync(~0u, s4[c], 1);
                s4[c] += __shfl_xor_sync(~0u, s4[c], 2);
            }
            const float mine = (lane & 2) ? ((lane & 1) ? s4[3] : s4[2]) : ((lane & 1) ? s4[1] : s4[0]);
            asm volatile("red.shared.add.f32 [%0],%1;" ::"r"(dest + grp * 128 + lane * 4), "f"(mine) : "memory");
        }
    }
}

__device__ __forceinline__ int fresh_warp() {
    int t;
    asm volatile("mov.u32 %0,%%tid.x;" : "=r"(t));
    return __shfl_sync(~0u, t >> 5, 0);
}
__device__ __forceinline__ int fresh_lane() {
    int t;
    asm volatile("mov.u32 %0,%%laneid;" : "=r"(t));
    return t;
}
template <int V> struct IC { static constexpr int v = V; };
constexpr float kLowBias = -19.0f;
constexpr float kSmallDen = 2e-5f;
constexpr int kSpinMax = 1 << 20;

__global__ void __launch_bounds__(kThreads, 1)
gatedgcn_kernel(const int* __restrict__ dst, const int* __restrict__ src, Scratch* __restrict__ scr,
                const __nv_bfloat16* __restrict__ x, const __nv_bfloat16* __restrict__ eattr,
                const __nv_bfloat16* __restrict__ wa, const __nv_bfloat16* __restrict__ wb,
                const __nv_bfloat16* __restrict__ wc, const __nv_bfloat16* __restrict__ wu,
                const __nv_bfloat16* __restrict__ wv, __nv_bfloat16* __restrict__ out) {
    extern __shared__ __align__(1024) unsigned char smem_raw[];
    const int tid = threadIdx.x;
    const int p = blockIdx.x;
    const int e0 = p * kCH;
    const int nch = min(kCH, kE - e0);
    const bool v2 = tid + 2 * kThreads < (nch >> 2);
    uint4 dv[3], sv[3];
    dv[2] = sv[2] = make_uint4(0, 0, 0, 0);
    ld_idx3(dv, dst + e0 + tid * 4, v2);
    const uint32_t sb = (uint32_t)__cvta_generic_to_shared(smem_raw);
    const int lane = tid & 31;
    const int warp = __shfl_sync(~0u, tid >> 5, 0), wg = warp >> 2, warp4 = warp & 3;
    const int node0 = p * kNPC;
    const int nown = min(kNPC, kN - node0);
    ld_idx3(sv, src + e0 + tid * 4, v2);
    const uint32_t woff = (tid >> 3) * 128 + (((tid ^ (tid >> 3)) & 7) << 4);
    const uint32_t wrot = (p & 7) * 1024;
    const uint32_t wgo = (tid * 16 + wrot) & 8191, wso = (woff + wrot) & 8191;
    if (tid < 96) sts32(sb + SC_CNT + tid * 4, 0);
    if (tid < 8) sts32(sb + SM_VARS + tid * 4, 0);
    {
        const uint32_t pad = kPad0 + (uint32_t)((tid & 15) % 9) * kPadStep;
#pragma unroll
        for (int i = 0; i < 5; i++)
            if (i < 4 || tid < 64) sts128(sb + SC_SORT + (tid + i * kThreads) * 16, make_uint4(pad, pad, pad, pad));
        __syncwarp();
        int c = 2 * warp + (lane & 1) + 32 * (lane >> 1);
        if (c < kCTAs) sts32(sb + SC_SORT + c * 256 + (c & 63) * 4, kCntBase);
    }
    if (tid == 320) {
        if (sb & 1023u) __trap();
#pragma unroll
        for (int i = 0; i < kNWG * kStages; i++) {
            mbar_init(sb + SM_BAR + i * 8, 65);
            mbar_init(sb + SM_BAR + 96 + i * 8, 4);
        }
    }
    __syncthreads();

    {
        const uint32_t dd[12] = {dv[0].x, dv[0].y, dv[0].z, dv[0].w, dv[1].x, dv[1].y, dv[1].z, dv[1].w, dv[2].x, dv[2].y, dv[2].z, dv[2].w};
        uint32_t c[12], r[12], w[12];
#pragma unroll
        for (int j = 0; j < 8; j++) {
            c[j] = (dd[j] * 55189u) >> 22;
            r[j] = atoms_inc(sb + SC_SORT + c[j] * 256 + (c[j] & 63) * 4);
        }
        if (v2) {
#pragma unroll
            for (int j = 8; j < 12; j++) {
                c[j] = (dd[j] * 55189u) >> 22;
                r[j] = atoms_inc(sb + SC_SORT + c[j] * 256 + (c[j] & 63) * 4);
            }
        } else {
#pragma unroll
            for (int j = 8; j < 12; j++) c[j] = r[j] = 0;
        }
        const int k = tid >> 3;
        cp16_z(sb + SC_XOWN + woff, reinterpret_cast<const char*>(x) + (size_t)node0 * 128 + (k < nown ? tid * 16 : 0), k >= nown);
        if (tid < 128) cp16_z(sb + SC_XOWN + 8192 + woff, reinterpret_cast<const char*>(x) + (size_t)node0 * 128 + (k + 64 < nown ? 8192 + tid * 16 : 0), k + 64 >= nown);
        cp16(sb + SC_WA + wso, reinterpret_cast<const char*>(wa) + wgo);
        cp16(sb + SC_WU + wso, reinterpret_cast<const char*>(wu) + wgo);
        asm volatile("cp.async.commit_group;" ::: "memory");
        cp16(sb + SC_WB + wso, reinterpret_cast<const char*>(wb) + wgo);
        cp16(sb + SC_WV + wso, reinterpret_cast<const char*>(wv) + wgo);
        if (tid < 128) cp16(sb + SC_WC + woff, reinterpret_cast<const char*>(wc) + tid * 16);
        asm volatile("cp.async.commit_group;" ::: "memory");
        const uint32_t ss[12] = {sv[0].x, sv[0].y, sv[0].z, sv[0].w, sv[1].x, sv[1].y, sv[1].z, sv[1].w, sv[2].x, sv[2].y, sv[2].z, sv[2].w};
        uint32_t rmax = 0;
#pragma unroll
        for (int j = 0; j < 12; j++) {
            uint32_t idx = ((dd[j] - c[j] * kNPC) * kRE + (tid * 4 + (j >> 2) * (4 * kThreads) + (j & 3))) * kRS + ss[j];
            w[j] = idx + __umulhi(idx, kRD) + 1;
            sts32_if(sb + SC_SORT + c[j] * 256 + ((c[j] + r[j]) & 63) * 4, w[j], r[j] < kCntBase + kCap - 1 && (j < 8 || v2));
            rmax = max(rmax, r[j]);
        }
        proxy_fence();
        __syncthreads();
        if (tid == kThreads - 1) {
            asm volatile("cp.async.bulk.global.shared::cta.bulk_group [%0],[%1],%2;" ::"l"(scr->rec + (size_t)p * kCTAs * kCap), "r"(sb + SC_SORT), "n"(kCTAs * kCap * 4) : "memory");
            asm volatile("cp.async.bulk.commit_group;" ::: "memory");
        }
        if (rmax >= kCntBase + kCap - 1) {
#pragma unroll
            for (int j = 0; j < 12; j++) {
                if (r[j] >= kCntBase + kCap - 1) {
                    uint32_t o = atoms_inc(sb + SM_VARS + 0);
                    st_relaxed64(&scr->ovf[p * kCH + o], w[j], c[j] + 1);
                }
            }
        }
    }
    const int ow = (lane >> 3) * 8 + ((lane & 7) >> 1) + (lane & 1) * 4;
    if (lane < 28) {
#pragma unroll
        for (int i = 0; i < 5; i++) {
            const int r = warp + 16 * i;
            const uint32_t v = node0 + (r < nown ? r : 0);
            if (r < 76 || (r == 76 && lane < 2)) {
                sts128(sb + SM_ROW + r * kRowB + lane * 16, make_uint4(v, v, v, v));
                sts128(sb + SM_ROW + r * kRowB + kEidOff + lane * 16, make_uint4(~0u, ~0u, ~0u, ~0u));
            }
        }
    }
    if (tid < 384) sts128(sb + SM_FLAG + tid * 16, make_uint4(0, 0, 0, 0));
    if (tid >= 480) sts128(sb + SM_PATCH + (tid - 480) * 16, make_uint4(0, 0, 0, 0));
    if (tid < kTMax) {
        constexpr uint32_t dm = (76 * kRowB / 16) * 0x10001u;
        sts128(sb + SM_OTAB + tid * 16, make_uint4(dm, dm, dm, dm));
    }
    if (tid >= 352 && tid < 352 + 24) sts32(sb + SM_LFIRST + (tid - 352) * 4, nown);
    if (tid >= 384 && tid < 448) {
        int s = tid & 7;
        uint32_t v = (s & 1) ? 0x3F800000u : 0x00003F80u;
        int w = s >> 1;
        sts128(sb + SM_IDENT + (tid - 384) * 16, make_uint4(w == 0 ? v : 0, w == 1 ? v : 0, w == 2 ? v : 0, w == 3 ? v : 0));
    }
    asm volatile("cp.async.wait_group 1;" ::: "memory");
    proxy_fence();
    __syncthreads();
    const int l16 = lane & 15;
    const int peer0 = 2 * warp + (lane >> 4);
    uint4 rv[4];
    uint32_t rx = tid < 256 ? 0 : kPad0 + (uint32_t)(lane % 9) * kPadStep;
    const char* gsrc = reinterpret_cast<const char*>(scr->rec) + ((size_t)peer0 * kCTAs + p) * (kCap * 4) + l16 * 16;
    const unsigned int* gsrx = scr->rec + ((size_t)(128 + ((tid >> 6) & 3)) * kCTAs + p) * kCap + (tid & 63);
    {
        uint32_t af[4][4];
#pragma unroll
        for (int ks = 0; ks < 4; ks++) load_wfrag(af[ks], sb + ((wg & 2) ? SC_WU : SC_WA), ks, warp4, lane);
        float d[20];
        uint64_t dx = mkdesc(sb + SC_XOWN + (wg & 1) * 5120, 16, 1024, 1);
        wg_fence();
#pragma unroll
        for (int ks = 0; ks < 4; ks++) wgmma_n40(d, af[ks], dx + ks * 2, ks > 0);
        wg_commit();
        wg_wait<0>();
        fence_regs(d);
        if (wg < 2) {
            uint32_t lo = 0, hi = 0;
#pragma unroll
            for (int i = 0; i < 10; i++) {
                const uint32_t bit = fminf(d[(i >> 1) * 4 + (i & 1)], d[(i >> 1) * 4 + 2 + (i & 1)]) < kLowBias ? 1u << (((i >> 1) & 3) * 8 + (i & 1)) : 0u;
                if (i < 8) lo |= bit;
                else hi |= bit;
            }
            lo = __reduce_or_sync(~0u, lo << ((lane & 3) * 2));
            hi = __reduce_or_sync(~0u, hi << ((lane & 3) * 2));
            if (lane < 2) sts32(sb + SM_LOW + (warp4 * 4 + wg * 2 + lane) * 4, lane ? hi : lo);
        }
        float sc = (wg & 2) ? 1.0f : 0.5f;
        uint32_t tb = sb + ((wg & 2) ? SC_UTAB : SM_ATAB) + ((wg & 1) * 40 + (lane & 3) * 2) * kTabB + (warp4 * 8 + (lane >> 2)) * 4;
#pragma unroll
        for (int j = 0; j < 5; j++) {
            const bool keep = j < 4 || wg != 1 || (lane & 3) < 3;
            sts32_if(tb + j * 8 * kTabB, pack_bf16(d[4 * j] * sc, d[4 * j + 2] * sc), keep);
            sts32_if(tb + j * 8 * kTabB + kTabB, pack_bf16(d[4 * j + 1] * sc, d[4 * j + 3] * sc), keep);
        }
    }
    if (tid == kThreads - 1) asm volatile("cp.async.bulk.wait_group 0;" ::: "memory");
    asm volatile("cp.async.wait_group 0;" ::: "memory");
    __syncthreads();

#pragma unroll
    for (int k = 0; k < 4; k++) {
        rv[k] = make_uint4(0, 0, 0, 0);
        ld_relaxed128_if(rv[k], gsrc + (size_t)k * (32 * kCTAs * kCap * 4), true);
    }
    if (rx == 0) rx = ld_relaxed32(gsrx);
    uint32_t fb[4][4], fv[4][4], fc[4];
    if (wg < kNWG) {
#pragma unroll
        for (int ks = 0; ks < 4; ks++) {
            load_wfrag(fb[ks], sb + SC_WB, ks, warp4, lane);
            load_wfrag(fv[ks], sb + SC_WV, ks, warp4, lane);
        }
        load_wfrag(fc, sb + SC_WC, 0, warp4, lane);
    }
    auto decode = [&](uint32_t rec, uint32_t ebase, uint32_t& ln, uint32_t& sr, uint32_t& eid) {
        unsigned long long t = (unsigned long long)rec * kRB;
        ln = (uint32_t)(t >> 32);
        t = (unsigned long long)(uint32_t)t * kRE + ((unsigned long long)ebase << 32);
        eid = (uint32_t)(t >> 32);
        sr = __umulhi((uint32_t)t, kRS);
    };
    {
#pragma unroll 1
        for (int spins = 0; spins < kSpinMax; spins++) {
            uint32_t m[4];
#pragma unroll
            for (int k = 0; k < 4; k++) m[k] = min(min(rv[k].x, rv[k].y), min(rv[k].z, rv[k].w));
            if (!__any_sync(~0u, min(min(m[0], m[1]), min(min(m[2], m[3]), rx)) == 0)) break;
#pragma unroll
            for (int k = 0; k < 4; k++) ld_relaxed128_if(rv[k], gsrc + (size_t)k * (32 * kCTAs * kCap * 4), m[k] == 0);
            if (rx == 0) rx = ld_relaxed32(gsrx);
        }
        uint32_t cmax = 0;
        if (l16 == ((p & 63) >> 2)) {
#pragma unroll
            for (int k = 0; k < 4; k++) {
                uint32_t h = ((p & 2) ? ((p & 1) ? rv[k].w : rv[k].z) : ((p & 1) ? rv[k].y : rv[k].x)) - kCntBase;
                sts32(sb + SM_HS + (peer0 + 32 * k) * 4, h);
                cmax = max(cmax, h);
            }
        }
        if (tid < 256 && (tid & 63) == (p & 63)) {
            sts32(sb + SM_HS + (128 + (tid >> 6)) * 4, rx - kCntBase);
            cmax = max(cmax, rx - kCntBase);
        }
        if (__any_sync(~0u, cmax >= kCap)) {
            sts32(sb + SM_VARS + 8, 1);
            __syncwarp();
#pragma unroll 1
            for (uint32_t j = 0; j < 9; j++) {
                const uint32_t sp = j < 8 ? 2 * warp + (j & 1) + 32 * (j >> 1) : 128 + (warp >> 1);
                if (j == 8 && (warp >= 8 || (warp & 1) != ((p >> 5) & 1))) break;
                uint32_t h = lds32(sb + SM_HS + sp * 4);
                if (h < kCap) continue;
                uint32_t need = h - (kCap - 1), lim = 0;
                uint2 r0;
                for (int spins = 0; spins < 65536; spins++) {
                    uint32_t found = 0;
                    for (lim = 0; lim < kCH && found < need; lim += 32) {
                        uint2 r = ld_relaxed64(&scr->ovf[sp * kCH + min(lim + lane, kCH - 1u)]);
                        if (lim == 0) r0 = r;
                        found += __popc(__ballot_sync(~0u, lim + lane < kCH && r.y == (uint32_t)p + 1));
                        if ((spins & 63) != 63 && !__any_sync(~0u, r.y != 0)) break;
                    }
                    if (found >= need) break;
                }
                for (uint32_t i = lane; i < min(lim, (uint32_t)kCH); i += 32) {
                    uint2 r = i < 32 ? r0 : ld_relaxed64(&scr->ovf[sp * kCH + i]);
                    if (r.y == (uint32_t)p + 1) {
                        uint32_t l, sc, e;
                        decode(r.x, sp * kCH, l, sc, e);
                        uint32_t k = atoms_inc(sb + SC_CNT + l * 4);
                        sts32x2_if(sb + SM_ROW + l * kRowB + k * 4, sc, e, k < kRowCap);
                    }
                }
                if (lane == 0) sts32(sb + SM_HS + sp * 4, h | (min(lim, (uint32_t)kCH) << 16));
            }
        }
        const uint32_t rec[17] = {rv[0].x, rv[0].y, rv[0].z, rv[0].w, rv[1].x, rv[1].y, rv[1].z, rv[1].w, rv[2].x,
                                  rv[2].y, rv[2].z, rv[2].w, rv[3].x, rv[3].y, rv[3].z, rv[3].w, rx};
#pragma unroll
        for (int k = 0; k < 5; k++) {
            const int nr = k < 4 ? 4 : 1;
            const uint32_t mn = k < 4 ? min(min(rec[4 * k], rec[4 * k + 1]), min(rec[4 * k + 2], rec[4 * k + 3])) : rec[16];
            if (mn < kPad0) {
                uint32_t ln[4], sr[4], ei[4], rr[4];
#pragma unroll
                for (int i = 0; i < nr; i++) {
                    decode(rec[4 * k + i], k < 4 ? (peer0 + 32 * k) * kCH : (128 + (tid >> 6)) * kCH, ln[i], sr[i], ei[i]);
                    rr[i] = atoms_inc(sb + SC_CNT + ln[i] * 4);
                }
#pragma unroll
                for (int i = 0; i < nr; i++) sts32x2_if(sb + SM_ROW + ln[i] * kRowB + rr[i] * 4, sr[i], ei[i], ln[i] < kNPC && rr[i] < kRowCap);
            }
        }
        __syncthreads();
    }
    uint32_t T;
    uint32_t opk = 0, oinc;
    bool slow;
    {
        uint32_t cm = 0;
#pragma unroll
        for (int j = 0; j < 3; j++) {
            int b = lane + 32 * j;
            uint32_t c = lds32(sb + SC_CNT + b * 4);
            c = b < nown ? max(c, 1u) : 0;
            cm = max(cm, c);
            opk |= ((min(c, (uint32_t)kRowCap) + 7) >> 3) << (10 * j);
        }
        oinc = opk;
#pragma unroll
        for (int d = 1; d < 32; d <<= 1) {
            uint32_t t = __shfl_up_sync(~0u, oinc, d);
            if (lane >= d) oinc += t;
        }
        const uint32_t tot = __shfl_sync(~0u, oinc, 31);
        const uint32_t s0 = tot & 1023, s01 = s0 + ((tot >> 10) & 1023);
        oinc += (s0 << 10) + (s01 << 20);
        T = max((s01 + (tot >> 20) + 7) >> 3, 3u);
        slow = T > kTMax || __any_sync(~0u, cm > kRowCap);
    }
    const uint32_t L0 = (T + 2) / 3, L1 = (T + 1) / 3, L2 = T / 3;
    const uint32_t B1 = 8 * L0, B2 = B1 + 8 * L1;
    const int ch = lane * 2;
    const int r2 = (ch >> 4) * 8 + (ch & 7), hf = (ch >> 3) & 1;

    if (slow) {
        __syncthreads();
        for (int i = tid; i < 76 * 128; i += kThreads) sts32(sb + SC_ACC + i * 4, 0);
        __syncthreads();
        float* acc = reinterpret_cast<float*>(smem_raw + SC_ACC);
#pragma unroll 1
        for (int sp = 0; sp < kCTAs; sp++) {
            uint32_t h = lds32(sb + SM_HS + sp * 4);
            uint32_t cnt = min(h & 0xFFFF, (uint32_t)kCap - 1);
            uint32_t tot = cnt + (h >> 16);
#pragma unroll 1
            for (uint32_t i = warp; i < tot; i += 16) {
                uint32_t rec;
                if (i < cnt) {
                    rec = ld_relaxed32(scr->rec + ((size_t)sp * kCTAs + p) * kCap + ((p + 1 + i) & 63));
                } else {
                    uint2 o = ld_relaxed64(&scr->ovf[sp * kCH + (i - cnt)]);
                    if (o.y != (uint32_t)p + 1) continue;
                    rec = o.x;
                }
                uint32_t eid, ln, s;
                decode(rec, sp * kCH, ln, s, eid);
                uint32_t xv = __ldg(reinterpret_cast<const uint32_t*>(x) + s * 32 + lane);
                uint32_t ev = __ldg(reinterpret_cast<const uint32_t*>(eattr) + (size_t)eid * 8 + (lane & 7));
                float g0 = 0.f, g1 = 0.f, h0 = 0.f, h1 = 0.f;
#pragma unroll 2
                for (int k = 0; k < 64; k++) {
                    uint32_t xx = __shfl_sync(~0u, xv, k >> 1);
                    float xf = (k & 1) ? bf_hi(xx) : bf_lo(xx);
                    uint32_t off = k * 128 + (((ch >> 3) ^ (k & 7)) << 4) + (ch & 7) * 2;
                    uint32_t b = lds32(sb + SC_WB + off), v = lds32(sb + SC_WV + off);
                    g0 = fmaf(xf, bf_lo(b), g0); g1 = fmaf(xf, bf_hi(b), g1);
                    h0 = fmaf(xf, bf_lo(v), h0); h1 = fmaf(xf, bf_hi(v), h1);
                }
#pragma unroll 2
                for (int k = 0; k < 16; k++) {
                    uint32_t ee = __shfl_sync(~0u, ev, k >> 1);
                    float ef = (k & 1) ? bf_hi(ee) : bf_lo(ee);
                    uint32_t c = lds32(sb + SC_WC + k * 128 + (((ch >> 3) ^ (k & 7)) << 4) + (ch & 7) * 2);
                    g0 = fmaf(ef, bf_lo(c), g0); g1 = fmaf(ef, bf_hi(c), g1);
                }
                uint32_t a0 = lds32(sb + SM_ATAB + ln * kTabB + r2 * 4), a1 = lds32(sb + SM_ATAB + ln * kTabB + r2 * 4 + 4);
                float e0f = 2.0f * rcp_fast(1.0f + ex2_fast((0.5f * g0 + (hf ? bf_hi(a0) : bf_lo(a0))) * -2.885390082f));
                float e1f = 2.0f * rcp_fast(1.0f + ex2_fast((0.5f * g1 + (hf ? bf_hi(a1) : bf_lo(a1))) * -2.885390082f));
                float* ap = acc + ln * 128 + r2 * 4 + hf;
                atomicAdd(ap, e0f); atomicAdd(ap + 2, e0f * h0);
                atomicAdd(ap + 4, e1f); atomicAdd(ap + 6, e1f * h1);
            }
        }
        __syncthreads();
#pragma unroll 1
        for (int n = warp; n < nown; n += 16) {
            const float* ap = acc + n * 128 + r2 * 4 + hf;
            uint32_t u0 = lds32(sb + SC_UTAB + n * kTabB + r2 * 4), u1 = lds32(sb + SC_UTAB + n * kTabB + r2 * 4 + 4);
            uint32_t xv = __ldg(reinterpret_cast<const uint32_t*>(x) + (size_t)(node0 + n) * 32 + lane);
            float z0 = (hf ? bf_hi(u0) : bf_lo(u0)) + __fdividef(ap[2], ap[0] + 2e-6f);
            float z1 = (hf ? bf_hi(u1) : bf_lo(u1)) + __fdividef(ap[6], ap[4] + 2e-6f);
            reinterpret_cast<uint32_t*>(out)[(size_t)(node0 + n) * 32 + lane] = pack_bf16(bf_lo(xv) + fmaxf(z0, 0.f), bf_hi(xv) + fmaxf(z1, 0.f));
        }
        clear_slots(scr, p, warp, 16, lane);
        clear_overflow(scr, sb, p, warp, 16, lane);
        return;
    }

    {
        const uint32_t ia = __shfl_sync(~0u, oinc, warp), ib = __shfl_sync(~0u, oinc, warp + 16);
        const uint32_t pa = __shfl_sync(~0u, opk, warp), pb = __shfl_sync(~0u, opk, warp + 16);
#pragma unroll
        for (int i = 0; i < 5; i++) {
            const uint32_t cnt = (((i & 1) ? pb : pa) >> (10 * (i >> 1))) & 1023;
            const uint32_t end = (((i & 1) ? ib : ia) >> (10 * (i >> 1))) & 1023;
            if ((uint32_t)lane < cnt)
                asm volatile("st.shared.u16 [%0],%1;" ::"r"(sb + SM_OTAB + (end - cnt + lane) * 2), "h"((unsigned short)((warp + 16 * i) * (kRowB / 16) + 2 * lane)) : "memory");
        }
    }

    if (wg == kNWG) {
        asm volatile("setmaxnreg.dec.sync.aligned.u32 80;");
        const int warp4 = fresh_warp() & 3;
        asm volatile("bar.sync 5, 512;" ::: "memory");
        if (warp4 < kNWG) {
            const int a = lane >> 3, c = lane & 7;
            const uint64_t xg = reinterpret_cast<uint64_t>(x) + c * 16;
            const uint32_t L = warp4 == 0 ? L0 : warp4 == 1 ? L1 : L2;
            uint32_t ot = sb + SM_OTAB + ((warp4 == 0 ? 0 : warp4 == 1 ? B1 : B2) + 2 * a * L) * 2;
            const uint32_t ostep = L * 2;
            uint32_t o0 = lds16(ot), o1 = lds16(ot + ostep);
            const uint32_t d0 = sb + warp4 * kStages * kStageB + (2 * a) * 128 + ((c ^ (2 * a)) << 4);
            const uint32_t d1 = sb + warp4 * kStages * kStageB + (2 * a + 1) * 128 + ((c ^ (2 * a + 1)) << 4);
            const uint32_t bar = sb + SM_BAR + warp4 * kStages * 8;
            uint32_t st = 0, ph = 1;
            char* clr = reinterpret_cast<char*>(scr->rec) + ((size_t)(2 * warp4 + (lane >> 4)) * kCTAs + p) * (kCap * 4) + (lane & 15) * 16;
#pragma unroll 1
            for (uint32_t t = 0; t < L; t++) {
                const uint32_t l0 = sb + SM_ROW + o0 * 16, l1 = sb + SM_ROW + o1 * 16;
                uint4 s0 = lds128(l0), s1 = lds128(l0 + 16), s2 = lds128(l1), s3 = lds128(l1 + 16);
                ot += 2;
                o0 = lds16(ot);
                o1 = lds16(ot + ostep);
                mbar_wait(bar + 96 + st * 8, ph);
                uint32_t sa[8] = {s0.x, s0.y, s0.z, s0.w, s1.x, s1.y, s1.z, s1.w};
                uint32_t sc[8] = {s2.x, s2.y, s2.z, s2.w, s3.x, s3.y, s3.z, s3.w};
                const uint32_t so = st * kStageB;
#pragma unroll
                for (int m = 0; m < 8; m++) {
                    cp16_idx<128>(d0 + so + m * 1024, xg, sa[m]);
                    cp16_idx<128>(d1 + so + m * 1024, xg, sc[m]);
                }
                mbar_cp_arrive(bar + st * 8);
                if (t >= kStages && t < kStages + 22) {
                    asm volatile("st.global.v4.u32 [%0],{%1,%1,%1,%1};" ::"l"(clr), "r"(0) : "memory");
                    clr += 3 * 2 * kCTAs * kCap * 4;
                }
                if (t == kStages + 1 && lds32(sb + SM_VARS + 8)) clear_overflow(scr, sb, p, warp4, 3, lane);
                if (++st == kStages) { st = 0; ph ^= 1; }
            }
            if (L < kStages + 22) clear_slots(scr, p, warp4 + 3 * max((int)L - kStages, 0), 3, lane);
            if (L < kStages + 2 && lds32(sb + SM_VARS + 8)) clear_overflow(scr, sb, p, warp4, 3, lane);
        } else {
            const int hh = lane >> 1, s = hh & 7, jb = (hh >> 3) * 4, half = lane & 1;
            const uint64_t eg = reinterpret_cast<uint64_t>(eattr) + half * 16;
            const uint32_t la = sb + SM_ROW + kEidOff + jb * 4;
            const uint32_t fsel = half ? 7 : 3;
            uint32_t ot[3] = {sb + SM_OTAB + s * L0 * 2, sb + SM_OTAB + (B1 + s * L1) * 2, sb + SM_OTAB + (B2 + s * L2) * 2};
            uint32_t ov[3] = {lds16(ot[0]), lds16(ot[1]), lds16(ot[2])};

            const uint32_t de = sb + 8192 + (jb * 8 + s) * 32 + ((half ^ (s >> 2)) << 4);
            const uint32_t df = sb + SM_FLAG + ((jb + half * 2) * 8 + s) * 16 + ((jb >> 1) + half) * 4 + 1;
            uint32_t st = 0, ph = 1;
#pragma unroll 1
            for (uint32_t t = 0; t < L0; t++) {
#pragma unroll
                for (int w = 0; w < kNWG; w++) {
                    if (3 * t + w >= T) break;
                    uint4 ev = lds128(la + ov[w] * 16);
                    ov[w] = lds16(ot[w] + (t + 1) * 2);
                    const uint32_t bi = w * kStages + st;
                    mbar_wait(sb + SM_BAR + 96 + bi * 8, ph);
                    const uint32_t so = bi * kStageB;
                    uint32_t ee[4] = {ev.x, ev.y, ev.z, ev.w};
                    asm volatile("st.shared.u8 [%0],%1;\nst.shared.u8 [%0+128],%2;"
                                 ::"r"(df + (bi >> 1) * 1024 + (bi & 1) * 2), "r"(__byte_perm(ee[0], ee[2], fsel)), "r"(__byte_perm(ee[1], ee[3], fsel)) : "memory");
#pragma unroll
                    for (int i = 0; i < 4; i++) cp16_idx_z<32>(de + so + i * 256, eg, ee[i]);
                    proxy_fence();
                    __syncwarp();
                    if (lane == 0) asm volatile("mbarrier.arrive.shared.b64 _,[%0];" ::"r"(sb + SM_BAR + bi * 8) : "memory");
                    mbar_cp_arrive(sb + SM_BAR + bi * 8);
                }
                if (++st == kStages) { st = 0; ph ^= 1; }
            }
        }
        asm volatile("bar.sync 7, 512;" ::: "memory");
        {
            const int lane = fresh_lane();
            uint32_t lm = lane < 16 ? lds32(sb + SM_LOW + lane * 4) : 0, keep = 0;
            lm |= __shfl_xor_sync(~0u, lm, 4);
            lm |= __shfl_xor_sync(~0u, lm, 8);
            if (lane >= 4) lm = 0;
            bool final_sums = false, stored = false;
#pragma unroll 1
            for (int round = 0; round < 2; round++, lm = keep) {
#pragma unroll 1
                for (uint32_t wm = __ballot_sync(~0u, lm != 0); wm; wm = __ballot_sync(~0u, lm != 0)) {
                    const int wi = __ffs(wm) - 1;
                    const uint32_t m = __shfl_sync(~0u, lm, wi);
                    const uint32_t n = ((wi & 2) ? 40 : 0) + ((wi & 1) ? 32 : 0) + __ffs(m) - 1;
                    if (lane == wi) lm &= lm - 1;
                    const uint32_t i0 = lds32(sb + SM_NINFO + n * 4);
                    auto small = [&]() {
                        const uint32_t l = (i0 >> 16) & 31;
                        const uint4 v = lds128(sb + (i0 & 0xFFFF) * 16 + lane * 16), t4 = lds128(sb + (l >> 3) * (kStages * kStageB) + (l & 7) * 528 + lane * 16);
                        const bool tail = final_sums && i0 >= (1u << 24);
                        return __ballot_sync(~0u, fminf(__uint_as_float(v.x) + (tail ? __uint_as_float(t4.x) : 0.f),
                                                        __uint_as_float(v.y) + (tail ? __uint_as_float(t4.y) : 0.f)) < kSmallDen);
                    };
                    uint32_t rows = (final_sums || (i0 & (1u << 22))) ? small() : ~0u;
                    if ((i0 & (1u << 23)) || rows == 0) continue;
                    if (round == 0) {
                        if (lane == wi + ((i0 & (1u << 22)) ? 0 : 4)) keep |= m & -m;
                        continue;
                    }
                    const int ow = (lane >> 3) * 8 + ((lane & 7) >> 1) + (lane & 1) * 4;
                    const uint32_t xv = __ldg(reinterpret_cast<const uint32_t*>(x) + (size_t)(node0 + n) * 32 + ow);
                    auto gate = [&]() -> uint32_t {
                        if (!final_sums) {
                            asm volatile("bar.sync 6, 512;" ::: "memory");
                            final_sums = true;
                            rows = small();
                        }
                        return rows;
                    };
                    exact_node(gate, sb, src, x, eattr, warp4, lane, n, sb + SM_PATCH);
                    if (rows == 0) continue;
                    if (!stored) asm volatile("bar.sync 8, 512;" ::: "memory");
                    else asm volatile("bar.sync 9, 128;" ::: "memory");
                    stored = true;
                    if (warp4 == 0) {
                        const uint4 v = lds128(sb + SM_PATCH + lane * 16);
                        const uint32_t u = lds32(sb + (((n % 12) >> 2) * kStages + 2) * kStageB + (((n % 12) & 3) * 7 + n / 12) * 128 + lane * 4);
                        const uint32_t o = finish_pair(make_float4(__uint_as_float(v.x), __uint_as_float(v.y), __uint_as_float(v.z), __uint_as_float(v.w)), u, xv, lane);
                        if ((rows >> (lane & 24)) & 0xFF) reinterpret_cast<uint32_t*>(out)[(size_t)(node0 + n) * 32 + ow] = o;
                        sts128(sb + SM_PATCH + lane * 16, make_uint4(0, 0, 0, 0));
                    }
                    asm volatile("bar.sync 9, 128;" ::: "memory");
                }
            }
            if (!final_sums) asm volatile("bar.arrive 6, 512;" ::: "memory");
            if (!stored) asm volatile("bar.arrive 8, 512;" ::: "memory");
            asm volatile("bar.arrive 10, 512;" ::: "memory");
        }
        asm volatile("cp.async.wait_all;" ::: "memory");
    } else {
        asm volatile("bar.arrive 5, 512;" ::: "memory");
        asm volatile("setmaxnreg.inc.sync.aligned.u32 144;");
        const int warp = fresh_warp(), wg = warp >> 2, warp4 = warp & 3;
        if (warp4 == 0) {
            const uint32_t b = (oinc >> (10 * wg)) & 1023, a = b - ((opk >> (10 * wg)) & 1023);
            const int n = lane + 32 * wg;
            auto lane_of = [&](uint32_t o, uint32_t& rem) {
                uint32_t w = (o >= B1) + (o >= B2);
                uint32_t oo = o - (w == 0 ? 0 : w == 1 ? B1 : B2), Lw = w == 0 ? L0 : w == 1 ? L1 : L2;
                uint32_t sl = __float2uint_rz(__fdividef((float)oo + 0.5f, (float)Lw));
                rem = oo - sl * Lw;
                return w * 8 + sl;
            };
            if (n <= nown) sts32(sb + SM_OEND + n * 4, n < nown ? b : 0x7FFFFFFFu);
            if (n < nown) {
                uint32_t ra, rb;
                const uint32_t la = lane_of(a, ra), lb = lane_of(b - 1, rb);
                const uint32_t fin = (la < lb || ra == 0) ? SM_HEAD + lb * 512 : SM_ROW + n * kRowB;
                const uint32_t deg = lds32(sb + SC_CNT + n * 4);
                const uint32_t lw = sb + SM_LOW + (n < 32 ? 0 : n < 40 ? 4 : n < 72 ? 8 : 12);
                const uint32_t lowb = ((lds32(lw) | lds32(lw + 16) | lds32(lw + 32) | lds32(lw + 48)) >> ((n < 40 ? n : n - 40) & 31)) & 1;
                const uint32_t inf = (fin >> 4) | (la << 16) | ((lb - la) << 24) | (deg ? 0u : 1u << 23) | (rb + 6 <= L2 ? 1u << 22 : 0u) | (lowb << 21);
                sts32(sb + SM_NINFO + n * 4, inf);
                asm volatile("st.shared.u8 [%0],%1;" ::"r"(sb + SM_DEG + n), "r"(deg) : "memory");
                for (uint32_t l = ra == 0 ? la : la + 1; l <= lb; l++) sts32(sb + SM_LFIRST + l * 4, n);
            }
            __syncwarp();
        }
        uint32_t uu[7];
#pragma unroll
        for (int j = 0; j < 4; j++) {
            fc[j] = half_bf16x2(fc[j]);
#pragma unroll
            for (int ks = 0; ks < 4; ks++) fb[ks][j] = half_bf16x2(fb[ks][j]);
        }
#pragma unroll
        for (int i = 0; i < 7; i++) {
            uint32_t ua = sb + SC_UTAB + min(warp + i * 12, 79) * kTabB + (lane & ~1) * 4;
            uu[i] = __byte_perm(lds32(ua), lds32(ua + 4), (lane & 1) ? 0x7632 : 0x5410);
        }
        asm volatile("bar.arrive 7, 512;" ::: "memory");
        asm volatile("bar.sync 1, 384;" ::: "memory");
        const int q = lane & 3;
        const int row = warp4 * 8 + (lane >> 2);
        uint32_t fa[4];
        const uint32_t lam = wg * 8 + q * 2;
        uint32_t cur0 = lds32(sb + SM_LFIRST + lam * 4) * 4, cur1 = lds32(sb + SM_LFIRST + lam * 4 + 4) * 4;
        const uint32_t L = wg == 0 ? L0 : wg == 1 ? L1 : L2;
        uint32_t ob0 = (wg == 0 ? 0 : wg == 1 ? B1 : B2) + q * 2 * L, ob1 = ob0 + L;
        uint32_t atab = sb + SM_ATAB + row * 4;
        uint32_t acct = sb + SM_ROW + kRowB + row * 16;
        uint32_t nx0 = sb + SM_HEAD + lam * 512 + row * 16, nx1 = nx0 + 512;
        uint32_t tend0 = lds32(sb + SM_OEND + cur0) - ob0, tend1 = lds32(sb + SM_OEND + cur1) - ob1;
        float num[4] = {0.f, 0.f, 0.f, 0.f}, den[4] = {0.f, 0.f, 0.f, 0.f};
        {
            uint32_t a0 = lds32(atab + cur0 * (kTabB / 4)), a1 = lds32(atab + cur1 * (kTabB / 4));
            fa[2] = __byte_perm(a0, a1, 0x5410);
            fa[3] = __byte_perm(a0, a1, 0x7632);
        }
        const uint32_t fbar = sb + SM_BAR + wg * kStages * 8;
        const uint32_t stage0 = sb + wg * kStages * kStageB;
        const uint64_t dx0 = mkdesc(stage0, 16, 1024, 1);
        const uint64_t de0 = mkdesc(stage0 + 8192, 16, 256, 3);
        const uint64_t df0 = mkdesc(0, 0, 128, 0) |
                             (uint32_t)__shfl_sync(~0u, (uint32_t)mkdesc(sb + SM_FLAG + wg * kStages * 512, SM_IDENT - SM_FLAG - wg * kStages * 512, 0, 0) + lane, 0);
        uint32_t oend = sb + SM_OEND + 4;
        atab += kTabB;
        asm volatile("" : "+r"(atab), "+r"(acct), "+r"(ob0), "+r"(ob1));
        uint32_t ebar = lane == 0 ? fbar + 96 : 0;
        asm volatile("" : "+r"(ebar));
        float g[32], h[32];
        uint32_t ph = 0, t = 1;
        mbar_wait(fbar, 0);
        proxy_fence();
        uint32_t sa0 = 0, sa1 = 0;
        uint32_t av0 = 0, av1 = 0;
        auto flush = [&]() {
            asm volatile(
                "{\n.reg .pred p,q;\nsetp.ne.u32 p,%8,0;\nsetp.ne.u32 q,%9,0;\n"
                "@p st.shared.v4.f32 [%8],{%0,%2,%4,%6};\n@q st.shared.v4.f32 [%9],{%1,%3,%5,%7};\n"
                "@p mov.f32 %0,0f00000000;\n@p mov.f32 %2,0f00000000;\n@p mov.f32 %4,0f00000000;\n@p mov.f32 %6,0f00000000;\n"
                "@q mov.f32 %1,0f00000000;\n@q mov.f32 %3,0f00000000;\n@q mov.f32 %5,0f00000000;\n@q mov.f32 %7,0f00000000;\n}"
                : "+f"(den[0]), "+f"(den[1]), "+f"(den[2]), "+f"(den[3]), "+f"(num[0]), "+f"(num[1]), "+f"(num[2]), "+f"(num[3])
                : "r"(sa0), "r"(sa1)
                : "memory");
        };
        auto tile = [&](auto stc) -> bool {
            constexpr int st = decltype(stc)::v;
            constexpr uint64_t kAdv = kStageB >> 4;
            fa[0] = fa[1] = (st & 1) ? 0x3F800000u : 0x00003F80u;
            wg_fence();
            wgmma_n64(g, fc, de0 + st * kAdv, 0);
            wgmma_n64(g, fa, df0 + (st >> 1) * 64 - ((uint64_t)((st >> 1) * 64) << 16), 1);
#pragma unroll
            for (int k = 0; k < 4; k++) wgmma_n64(g, fb[k], dx0 + st * kAdv + k * 2, 1);
            wg_commit();
#pragma unroll
            for (int k = 0; k < 4; k++) wgmma_n64(h, fv[k], dx0 + st * kAdv + k * 2, k > 0);
            wg_commit();
            auto fetch = [&]() {
                asm volatile(
                    "{\n.reg .pred p,q;\n"
                    "setp.eq.u32 p,%10,%4;\nsetp.eq.u32 q,%10,%5;\n"
                    "selp.u32 %2,%8,0,p;\nselp.u32 %3,%9,0,q;\n"
                    "@p mad.lo.u32 %0,%6,36,%11;\n@p ld.shared.u32 %0,[%0];\n@p add.u32 %4,%6,%13;\n@p ld.shared.u32 %4,[%4];\n"
                    "@p mad.lo.u32 %8,%6,244,%12;\n@p add.u32 %6,%6,4;\n"
                    "@q mad.lo.u32 %1,%7,36,%11;\n@q ld.shared.u32 %1,[%1];\n@q add.u32 %5,%7,%13;\n@q ld.shared.u32 %5,[%5];\n"
                    "@q mad.lo.u32 %9,%7,244,%12;\n@q add.u32 %7,%7,4;\n}"
                    : "+r"(av0), "+r"(av1), "=r"(sa0), "=r"(sa1), "+r"(tend0), "+r"(tend1), "+r"(cur0), "+r"(cur1), "+r"(nx0), "+r"(nx1)
                    : "r"(t), "r"(atab), "r"(acct), "r"(oend)
                    : "memory");
                static_assert(kRowB == 244 * 4 && kTabB == 36 * 4, "strides");
            };
            auto advance = [&]() {
                asm volatile(
                    "{\n.reg .pred p,q;\nsetp.ne.u32 p,%6,0;\nsetp.ne.u32 q,%7,0;\n"
                    "@p prmt.b32 %0,%0,%4,0x3254;\n@p prmt.b32 %1,%1,%4,0x3276;\n"
                    "@q prmt.b32 %0,%0,%5,0x5410;\n@q prmt.b32 %1,%1,%5,0x7610;\n"
                    "@p sub.u32 %2,%2,%8;\n@q sub.u32 %3,%3,%9;\n}"
                    : "+r"(fa[2]), "+r"(fa[3]), "+r"(tend0), "+r"(tend1) : "r"(av0), "r"(av1), "r"(sa0), "r"(sa1), "r"(ob0), "r"(ob1));
            };
            const bool last = t == L;
            if (st == kStages - 1) ph ^= 1;
            const uint32_t nbar = fbar + ((st + 1) % kStages) * 8;
            wg_wait<1>();
            fence_regs(g);
            fetch();
#pragma unroll
            for (int i = 0; i < 32; i++) {
                g[i] = 1.0f + tanh_fast(g[i]);
                den[i & 3] += g[i];
            }
            wg_wait<0>();
            fence_regs(h);
            advance();
            asm volatile("{\n.reg .pred p;\nsetp.ne.u32 p,%0,0;\n@p mbarrier.arrive.shared.b64 _,[%1];\n}" ::"r"(ebar), "r"(ebar + st * 8) : "memory");
            uint32_t ready = mbar_test(nbar, ph);
#pragma unroll
            for (int i = 0; i < 32; i++) num[i & 3] = fmaf(g[i], h[i], num[i & 3]);
            flush();
            if (!last && !ready) mbar_wait(nbar, ph);
            t++;
            return last;
        };
        static_assert(kStages == 4, "unrolled ring");
#pragma unroll 1
        while (true) {
            if (tile(IC<0>{})) break;
            if (tile(IC<1>{})) break;
            if (tile(IC<2>{})) break;
            if (tile(IC<3>{})) break;
        }
        uint32_t xv[7], inf[7];
#pragma unroll
        for (int i = 0; i < 7; i++) {
            int n = min(warp + i * 12, nown - 1);
            xv[i] = __ldg(reinterpret_cast<const uint32_t*>(x) + (size_t)(node0 + n) * 32 + ow);
            inf[i] = lds32(sb + SM_NINFO + n * 4);
        }
        asm volatile("bar.sync %0, 128;" ::"r"(wg + 2) : "memory");
        {
            uint32_t tb = sb + wg * kStages * kStageB + q * 1056 + row * 16;
            sts128f(tb, den[0], den[2], num[0], num[2]);
            sts128f(tb + 528, den[1], den[3], num[1], num[3]);
#pragma unroll
            for (int i = 0; i < 7; i++) sts32(sb + (wg * kStages + 2) * kStageB + (warp4 * 7 + i) * 128 + lane * 4, uu[i]);
            const uint32_t wf = sb + (wg * kStages + 1) * kStageB + warp4 * 1536 + lane * 16;
#pragma unroll
            for (int i = 0; i < 3; i++) {
                const uint32_t(&a)[4] = i == 0 ? fb[0] : i == 1 ? fb[1] : fb[2];
                const uint32_t(&b)[4] = i == 0 ? fb[3] : i == 1 ? fv[0] : fv[1];
                const uint32_t(&c)[4] = i == 0 ? fv[2] : i == 1 ? fv[3] : fc;
                if (wg == 0) sts128(wf + i * 512, make_uint4(a[0], a[1], a[2], a[3]));
                if (wg == 1) sts128(wf + i * 512, make_uint4(b[0], b[1], b[2], b[3]));
                if (wg == 2) sts128(wf + i * 512, make_uint4(c[0], c[1], c[2], c[3]));
            }
        }
        asm volatile("bar.arrive 6, 512;" ::: "memory");
        asm volatile("bar.sync 1, 384;" ::: "memory");
        uint4 av[7], tl[7];
        uint32_t many = 0;
#pragma unroll
        for (int i = 0; i < 7; i++) {
            av[i] = lds128(sb + (inf[i] & 0xFFFF) * 16 + lane * 16);
            const uint32_t l = (inf[i] >> 16) & 31;
            tl[i] = lds128(sb + (l >> 3) * (kStages * kStageB) + (l & 7) * 528 + lane * 16);
            if (inf[i] < (1u << 24)) tl[i] = make_uint4(0, 0, 0, 0);
            many = max(many, inf[i]);
        }
        float4 sm[7];
#pragma unroll
        for (int i = 0; i < 7; i++)
            sm[i] = make_float4(__uint_as_float(av[i].x) + __uint_as_float(tl[i].x), __uint_as_float(av[i].y) + __uint_as_float(tl[i].y),
                                __uint_as_float(av[i].z) + __uint_as_float(tl[i].z), __uint_as_float(av[i].w) + __uint_as_float(tl[i].w));
        if (many >= (2u << 24)) {
#pragma unroll
            for (int i = 0; i < 7; i++) {
                uint32_t l0 = (inf[i] >> 16) & 31;
#pragma unroll 1
                for (uint32_t l = l0 + 1; l < l0 + (inf[i] >> 24); l++) {
                    uint4 t4 = lds128(sb + (l >> 3) * (kStages * kStageB) + (l & 7) * 528 + lane * 16);
                    sm[i].x += __uint_as_float(t4.x); sm[i].y += __uint_as_float(t4.y);
                    sm[i].z += __uint_as_float(t4.z); sm[i].w += __uint_as_float(t4.w);
                }
            }
        }
        auto finish = [&](int i, const float4& v) {
            const uint32_t o = finish_pair(v, uu[i], xv[i], lane);
            if (warp + i * 12 < nown) reinterpret_cast<uint32_t*>(out)[(size_t)(node0 + warp + i * 12) * 32 + ow] = o;
        };
        uint32_t redo = 0;
#pragma unroll
        for (int i = 0; i < 7; i++) {
            finish(i, sm[i]);
            if (fminf(sm[i].x, sm[i].y) < kSmallDen && !(inf[i] & (5u << 21))) redo |= 1u << i;
        }
        {
            asm volatile("bar.arrive 8, 512;" ::: "memory");
            uint32_t any;
            asm volatile("{\n.reg .pred p,q;\nsetp.ne.u32 p,%1,0;\nbar.red.or.pred q,1,384,p;\nselp.u32 %0,1,0,q;\n}" : "=r"(any) : "r"(redo) : "memory");
            if (any) {
                redo = __reduce_or_sync(~0u, redo);
                asm volatile("bar.sync 10, 512;" ::: "memory");
                const uint32_t mark = sb + SM_OEND, sums = sb + SM_ROW;
                if (lane < 7 && warp + lane * 12 < nown) sts32(mark + (warp + lane * 12) * 4, (redo >> lane) & 1);
                for (int i = tid; i < kNPC * 128; i += 384) sts32(sums + (i >> 7) * kRowB + (i & 127) * 4, 0);
                asm volatile("bar.sync 1, 384;" ::: "memory");
#pragma unroll 1
                for (int j = wg; j < nown; j += 3)
                    if (lds32(mark + j * 4)) exact_node([] { return ~0u; }, sb, src, x, eattr, warp4, lane, j, sums + j * kRowB);
                asm volatile("bar.sync 1, 384;" ::: "memory");
#pragma unroll
                for (int i = 0; i < 7; i++) {
                    if ((redo >> i) & 1) {
                        const uint4 t4 = lds128(sums + min(warp + i * 12, nown - 1) * kRowB + lane * 16);
                        finish(i, make_float4(__uint_as_float(t4.x), __uint_as_float(t4.y), __uint_as_float(t4.z), __uint_as_float(t4.w)));
                    }
                }
            }
        }
    }
}

__device__ float g_fb_tab[kN * 256];
__device__ float g_fb_acc[kN * 128];

__global__ void fb_nodes(const __nv_bfloat16* x, const __nv_bfloat16* wa, const __nv_bfloat16* wb, const __nv_bfloat16* wv,
                         const __nv_bfloat16* wu) {
    const int n = blockIdx.x, c = threadIdx.x & 63, m = threadIdx.x >> 6;
    const __nv_bfloat16* w = m == 0 ? wa : m == 1 ? wb : m == 2 ? wv : wu;
    float a = 0.f;
    for (int k = 0; k < 64; k++) a = fmaf(__bfloat162float(x[n * 64 + k]), __bfloat162float(w[k * 64 + c]), a);
    g_fb_tab[n * 256 + threadIdx.x] = a;
    if (threadIdx.x < 128) g_fb_acc[n * 128 + threadIdx.x] = 0.f;
}
__global__ void fb_edges(const __nv_bfloat16* eattr, const int* src, const int* dst, const __nv_bfloat16* wc) {
    const int e = blockIdx.x * 4 + (threadIdx.x >> 6), c = threadIdx.x & 63;
    const int s = src[e], d = dst[e];
    float g = g_fb_tab[d * 256 + c] + g_fb_tab[s * 256 + 64 + c];
    for (int k = 0; k < 16; k++) g = fmaf(__bfloat162float(eattr[(size_t)e * 16 + k]), __bfloat162float(wc[k * 64 + c]), g);
    const float eta = 1.0f / (1.0f + __expf(-g));
    atomicAdd(&g_fb_acc[d * 128 + c], eta);
    atomicAdd(&g_fb_acc[d * 128 + 64 + c], eta * g_fb_tab[s * 256 + 128 + c]);
}
__global__ void fb_out(const __nv_bfloat16* x, __nv_bfloat16* out) {
    const int n = blockIdx.x * 4 + (threadIdx.x >> 6), c = threadIdx.x & 63;
    const float z = g_fb_tab[n * 256 + 192 + c] + g_fb_acc[n * 128 + 64 + c] / (g_fb_acc[n * 128 + c] + 1e-6f);
    out[n * 64 + c] = __float2bfloat16(__bfloat162float(x[n * 64 + c]) + fmaxf(z, 0.f));
}

}

extern "C" void kernel_launch(void* const* d_in, const int* in_sizes, int n_in, void* d_out, int out_size) {
    const __nv_bfloat16* x = (const __nv_bfloat16*)d_in[0];
    const __nv_bfloat16* eattr = (const __nv_bfloat16*)d_in[1];
    const int* src = (const int*)d_in[2];
    const int* dst = (const int*)d_in[3];
    const __nv_bfloat16* wa = (const __nv_bfloat16*)d_in[4];
    const __nv_bfloat16* wb = (const __nv_bfloat16*)d_in[5];
    const __nv_bfloat16* wc = (const __nv_bfloat16*)d_in[6];
    const __nv_bfloat16* wu = (const __nv_bfloat16*)d_in[7];
    const __nv_bfloat16* wv = (const __nv_bfloat16*)d_in[8];
    static Scratch* scr = nullptr;
    static bool resident = false;
    if (!scr) {
        int dev = 0, sms = 0, per_sm = 0;
        cudaGetDevice(&dev);
        cudaDeviceGetAttribute(&sms, cudaDevAttrMultiProcessorCount, dev);
        cudaError_t e = cudaFuncSetAttribute(gatedgcn_kernel, cudaFuncAttributeMaxDynamicSharedMemorySize, SM_TOTAL);
        if (e == cudaSuccess) e = cudaOccupancyMaxActiveBlocksPerMultiprocessor(&per_sm, gatedgcn_kernel, kThreads, SM_TOTAL);
        resident = e == cudaSuccess && sms * per_sm >= kCTAs;
        (void)cudaGetLastError();
        cudaGetSymbolAddress((void**)&scr, g_scratch);
    }
    if (resident) {
        gatedgcn_kernel<<<kCTAs, kThreads, SM_TOTAL>>>(dst, src, scr, x, eattr, wa, wb, wc, wu, wv, (__nv_bfloat16*)d_out);
    } else {
        fb_nodes<<<kN, 256>>>(x, wa, wb, wv, wu);
        fb_edges<<<kE / 4, 256>>>(eattr, src, dst, wc);
        fb_out<<<kN / 4, 256>>>(x, (__nv_bfloat16*)d_out);
    }
}
```
